```python
import torch

def _softmax(x, axis=-1):
    return torch.softmax(x, dim=axis)

def _gelu(x):
    return torch.nn.functional.gelu(x, approximate='tanh')

def _silu(x):
    return torch.nn.functional.silu(x)

def _sigmoid(x):
    return torch.sigmoid(x)

def _layernorm(x, axis=-1, eps=1e-05):
    m = x.mean(dim=axis, keepdim=True)
    v = x.var(dim=axis, keepdim=True, unbiased=False)
    return (x - m) / torch.sqrt(v + eps)

def _scatter_add(tgt, idx, src, axis=0):
    return tgt.clone().index_add_(axis, idx, src)

def _segment_sum(src, seg, n):
    out = torch.zeros((n,) + src.shape[1:], dtype=src.dtype)
    return out.index_add_(0, seg, src)

def _pad(x, pw):
    flat = tuple((v for pair in reversed(pw) for v in pair))
    return torch.nn.functional.pad(x, flat)
kernel_name = 'gather_scatter__molecular_angular_painn__graph'

def setup_inputs():

    _w = lambda a: (lambda t: t.to(torch.bfloat16) if t.is_floating_point() else t)(torch.as_tensor(a))
    N, deg, D = (10000, 64, 64)
    n_rbf = max(16, 4)
    E = N * deg
    cutoff = 5.0
    freqs = (torch.arange(1, n_rbf + 1) * torch.pi / cutoff).to(float)
    return {'sv': _w((lambda *s: torch.randn(*s, dtype=torch.bfloat16) * 0.4)(N, 4, D) * 0.3), 'pos': _w((lambda *s: torch.randn(*s, dtype=torch.bfloat16) * 1.6)(N, 3) * 1.2), 'src': _w((lambda lo, hi, *s: torch.randint(lo, hi, s))(0, N, E).to(torch.int64)), 'dst': _w((lambda lo, hi, *s: torch.randint(lo, hi, s))(0, N, E).to(torch.int64)), 'freqs': _w(freqs), 'w_phi1': _w((lambda *s: torch.randn(*s, dtype=torch.bfloat16) * 3.2)(D, D) / D ** 0.5), 'w_phi2': _w((lambda *s: torch.randn(*s, dtype=torch.bfloat16) * 1.6)(D, 3 * D) / D ** 0.5), 'w_rbf': _w((lambda *s: torch.randn(*s, dtype=torch.bfloat16) * 1.6)(n_rbf, 3 * D) / n_rbf ** 0.5)}

def reference(sv, pos, src, dst, freqs, w_phi1, w_phi2, w_rbf):
    N, _, D = sv.shape
    E = src.shape[0]
    PI, cutoff = (3.141592653589793, 5.0)
    s, v = (sv[:, 0, :].clone(), sv[:, 1:, :].clone())
    r_vec = pos[src] - pos[dst]
    d = torch.sqrt((r_vec * r_vec).sum(-1) + 1e-08)
    r_hat = r_vec / d[:, None]
    rbf = torch.sin(d[:, None] * freqs[None, :]) / d[:, None]
    fcut = 0.5 * (torch.cos(PI * d / cutoff) + 1.0)
    fcut = torch.where(d < cutoff, fcut, 0.0 * d)
    Wf = rbf @ w_rbf * fcut[:, None]
    phi = (_silu(s @ w_phi1) @ w_phi2)[src]
    m = phi * Wf
    m_s, m_vv, m_vr = (m[:, :D].clone(), m[:, D:2 * D].clone(), m[:, 2 * D:].clone())
    ds = _segment_sum(m_s, dst, N)
    dv_e = m_vv[:, None, :] * v[src] + m_vr[:, None, :] * r_hat[:, :, None]
    dv = _segment_sum(dv_e.reshape(E, 3 * D), dst, N).reshape(N, 3, D)
    return sv + torch.concatenate([ds[:, None, :], dv], axis=1)
```

```cpp
#include <cuda_runtime.h>
#include <cuda_bf16.h>
#include <stdint.h>

namespace {

constexpr int D = 64;
constexpr int NRBF = 16;
constexpr int MAXN = 10000;
constexpr int MAXE = 640000;
constexpr int GRP = 8;
constexpr int MAXG = (MAXN + GRP - 1) / GRP;
constexpr int CAP = 768;
constexpr int CNT_STRIDE = 8;
constexpr int DBASE = 0x38C0;
constexpr int DEND = 0x40A0;
constexpr int NTAB = DEND - DBASE;
constexpr int ROWB = 640;

__device__ __align__(128) unsigned char g_tab[(size_t)MAXN * ROWB];
__device__ __align__(128) __nv_bfloat16 g_G[NTAB * NRBF];
__device__ __align__(128) uint4 g_rec[(size_t)MAXG * CAP];
__device__ __align__(128) uint4 g_ovf[MAXE];
__device__ __align__(128) int g_cnt[MAXG * CNT_STRIDE];
__device__ int g_ovf_cnt;

__device__ __forceinline__ uint32_t smem_u32(const void* p) { return (uint32_t)__cvta_generic_to_shared(p); }
__device__ __forceinline__ float bf16r(float x) { return __bfloat162float(__float2bfloat16_rn(x)); }
__device__ __forceinline__ uint32_t pack_bf16(float lo, float hi) {
    uint32_t r;
    asm("cvt.rn.bf16x2.f32 %0, %1, %2;" : "=r"(r) : "f"(hi), "f"(lo));
    return r;
}
__device__ __forceinline__ uint32_t hmul2(uint32_t a, uint32_t b) {
    uint32_t r;
    asm("mul.rn.bf16x2 %0, %1, %2;" : "=r"(r) : "r"(a), "r"(b));
    return r;
}
__device__ __forceinline__ uint32_t hfma2(uint32_t a, uint32_t b, uint32_t c) {
    uint32_t r;
    asm("fma.rn.bf16x2 %0, %1, %2, %3;" : "=r"(r) : "r"(a), "r"(b), "r"(c));
    return r;
}
__device__ __forceinline__ void mma16816(float (&c)[4], uint32_t a0, uint32_t a1, uint32_t a2, uint32_t a3,
                                         uint32_t b0, uint32_t b1) {
    asm volatile("mma.sync.aligned.m16n8k16.row.col.f32.bf16.bf16.f32 {%0,%1,%2,%3}, {%4,%5,%6,%7}, {%8,%9}, {%0,%1,%2,%3};"
                 : "+f"(c[0]), "+f"(c[1]), "+f"(c[2]), "+f"(c[3])
                 : "r"(a0), "r"(a1), "r"(a2), "r"(a3), "r"(b0), "r"(b1));
}
__device__ __forceinline__ void mma16816_z(float (&c)[4], uint32_t a0, uint32_t a1, uint32_t a2, uint32_t a3,
                                           uint32_t b0, uint32_t b1) {
    asm volatile("mma.sync.aligned.m16n8k16.row.col.f32.bf16.bf16.f32 {%0,%1,%2,%3}, {%4,%5,%6,%7}, {%8,%9}, {%10,%10,%10,%10};"
                 : "=f"(c[0]), "=f"(c[1]), "=f"(c[2]), "=f"(c[3])
                 : "r"(a0), "r"(a1), "r"(a2), "r"(a3), "r"(b0), "r"(b1), "f"(0.f));
}
__device__ __forceinline__ void ldsm4(uint32_t (&r)[4], uint32_t addr) {
    asm volatile("ldmatrix.sync.aligned.m8n8.x4.shared.b16 {%0,%1,%2,%3}, [%4];"
                 : "=r"(r[0]), "=r"(r[1]), "=r"(r[2]), "=r"(r[3]) : "r"(addr));
}
__device__ __forceinline__ void ldsm4t(uint32_t (&r)[4], uint32_t addr) {
    asm volatile("ldmatrix.sync.aligned.m8n8.x4.trans.shared.b16 {%0,%1,%2,%3}, [%4];"
                 : "=r"(r[0]), "=r"(r[1]), "=r"(r[2]), "=r"(r[3]) : "r"(addr));
}

constexpr int P_THREADS = 1024;
constexpr int P1_WARPS = 5;
constexpr int P3_THREADS = P_THREADS - 32 * P1_WARPS;
constexpr int P3_ITERS = 3;
constexpr int W1_PITCH = 144;
constexpr int W2_PITCH = 400;
constexpr int PS_POS = 0;
constexpr int PS_W1 = 60032;
constexpr int PS_W2 = PS_W1 + 64 * W1_PITCH;
constexpr int PS_BAR = PS_W2 + 64 * W2_PITCH;
constexpr int PS_TOTAL = PS_BAR + 16;

__global__ void __launch_bounds__(P_THREADS, 1)
prep_kernel(const __nv_bfloat16* __restrict__ sv, const __nv_bfloat16* __restrict__ pos,
            const int* __restrict__ src, const int* __restrict__ dst,
            const __nv_bfloat16* __restrict__ freqs, const __nv_bfloat16* __restrict__ w1,
            const __nv_bfloat16* __restrict__ w2, int N, int E) {
    extern __shared__ __align__(128) unsigned char smem[];
    const int tid = threadIdx.x, warp = tid >> 5, lane = tid & 31;
    asm volatile("griddepcontrol.launch_dependents;");
    const uint32_t bar = smem_u32(smem + PS_BAR);

    if (warp < P1_WARPS) {
        const int g = lane >> 2, t = lane & 3;
        const int tile = warp * gridDim.x + blockIdx.x;
        const int ntiles = (N + 15) >> 4;
        const int n0 = min(tile * 16 + g, N - 1), n1 = min(tile * 16 + g + 8, N - 1);
        uint4 x[2][4][2];
        if (tile < ntiles) {
#pragma unroll
            for (int c = 0; c < 4; c++) {
                const uint4* p0 = reinterpret_cast<const uint4*>(sv + ((size_t)n0 * 4 + c) * D + 16 * t);
                const uint4* p1 = reinterpret_cast<const uint4*>(sv + ((size_t)n1 * 4 + c) * D + 16 * t);
                x[0][c][0] = __ldg(p0); x[0][c][1] = __ldg(p0 + 1);
                x[1][c][0] = __ldg(p1); x[1][c][1] = __ldg(p1 + 1);
            }
        }
        for (int i = tid; i < 64 * 8; i += 32 * P1_WARPS) {
            int r = i >> 3, c = i & 7;
            *reinterpret_cast<uint4*>(smem + PS_W1 + r * W1_PITCH + c * 16) =
                __ldg(reinterpret_cast<const uint4*>(w1 + r * 64) + c);
        }
        for (int i = tid; i < 64 * 24; i += 32 * P1_WARPS) {
            int r = i / 24, c = i % 24;
            uint4 v = __ldg(reinterpret_cast<const uint4*>(w2 + r * 192) + c);
            int part = c >> 3, cc = c & 7;
            int tt = cc >> 1, j0 = (cc & 1) * 4;
            uint32_t* o = reinterpret_cast<uint32_t*>(smem + PS_W2 + r * W2_PITCH + part * 128);
            o[4 * (j0 + 0) + tt] = v.x; o[4 * (j0 + 1) + tt] = v.y;
            o[4 * (j0 + 2) + tt] = v.z; o[4 * (j0 + 3) + tt] = v.w;
        }
        asm volatile("bar.sync 1, %0;" ::"n"(32 * P1_WARPS) : "memory");
        if (tile < ntiles) {
            float a[8][4];
            const uint32_t* s0 = reinterpret_cast<const uint32_t*>(&x[0][0][0]);
            const uint32_t* s1 = reinterpret_cast<const uint32_t*>(&x[1][0][0]);
            {
                const int i = lane & 7, hi = (lane >> 3) & 1, nsel = lane >> 4;
#pragma unroll
                for (int q = 0; q < 4; q++) {
                    const int krow = 16 * (i >> 1) + 4 * q + (i & 1) + 2 * hi;
#pragma unroll
                    for (int jp = 0; jp < 4; jp++) {
                        uint32_t b[4];
                        ldsm4t(b, smem_u32(smem + PS_W1 + krow * W1_PITCH + (2 * jp + nsel) * 16));
                        if (q == 0) {
                            mma16816_z(a[2 * jp], s0[0], s1[0], s0[1], s1[1], b[0], b[1]);
                            mma16816_z(a[2 * jp + 1], s0[0], s1[0], s0[1], s1[1], b[2], b[3]);
                        } else {
                            mma16816(a[2 * jp], s0[2 * q], s1[2 * q], s0[2 * q + 1], s1[2 * q + 1], b[0], b[1]);
                            mma16816(a[2 * jp + 1], s0[2 * q], s1[2 * q], s0[2 * q + 1], s1[2 * q + 1], b[2], b[3]);
                        }
                    }
                }
            }
            uint32_t h[4][4];
#pragma unroll
            for (int j = 0; j < 8; j++) {
                float f[4];
#pragma unroll
                for (int e = 0; e < 4; e++) {
                    float z = bf16r(a[j][e]);
                    f[e] = z / (1.0f + expf(-z));
                }
                h[j >> 1][(j & 1) * 2 + 0] = pack_bf16(f[0], f[1]);
                h[j >> 1][(j & 1) * 2 + 1] = pack_bf16(f[2], f[3]);
            }
            const bool ok0 = tile * 16 + g < N, ok1 = tile * 16 + g + 8 < N;
            unsigned char* row0 = g_tab + (size_t)n0 * ROWB + t * 32;
            unsigned char* row1 = g_tab + (size_t)n1 * ROWB + t * 32;
#pragma unroll
            for (int part = 0; part < 3; part++) {
                float p[8][4];
                const int i = lane & 15, nsel = lane >> 4;
#pragma unroll
                for (int q = 0; q < 4; q++) {
#pragma unroll
                    for (int jp = 0; jp < 4; jp++) {
                        uint32_t b[4];
                        ldsm4t(b, smem_u32(smem + PS_W2 + (16 * q + i) * W2_PITCH + part * 128 + (2 * jp + nsel) * 16));
                        if (q == 0) {
                            mma16816_z(p[2 * jp], h[0][0], h[0][1], h[0][2], h[0][3], b[0], b[1]);
                            mma16816_z(p[2 * jp + 1], h[0][0], h[0][1], h[0][2], h[0][3], b[2], b[3]);
                        } else {
                            mma16816(p[2 * jp], h[q][0], h[q][1], h[q][2], h[q][3], b[0], b[1]);
                            mma16816(p[2 * jp + 1], h[q][0], h[q][1], h[q][2], h[q][3], b[2], b[3]);
                        }
                    }
                }
#pragma unroll
                for (int r = 0; r < 2; r++) {
                    unsigned char* row = r ? row1 : row0;
                    const bool ok = r ? ok1 : ok0;
                    if (part != 1) {
                        uint4 ev, od;
                        ev.x = pack_bf16(p[0][2 * r], p[1][2 * r]); ev.y = pack_bf16(p[2][2 * r], p[3][2 * r]);
                        ev.z = pack_bf16(p[4][2 * r], p[5][2 * r]); ev.w = pack_bf16(p[6][2 * r], p[7][2 * r]);
                        od.x = pack_bf16(p[0][2 * r + 1], p[1][2 * r + 1]); od.y = pack_bf16(p[2][2 * r + 1], p[3][2 * r + 1]);
                        od.z = pack_bf16(p[4][2 * r + 1], p[5][2 * r + 1]); od.w = pack_bf16(p[6][2 * r + 1], p[7][2 * r + 1]);
                        if (ok) {
                            uint4* o = reinterpret_cast<uint4*>(row + (part == 0 ? 0 : 4) * 128);
                            o[0] = ev; o[1] = od;
                        }
                    } else {
                        uint32_t pv[8];
#pragma unroll
                        for (int j = 0; j < 8; j++) pv[j] = pack_bf16(p[j][2 * r], p[j][2 * r + 1]);
#pragma unroll
                        for (int c = 1; c < 4; c++) {
                            const uint32_t* vv = reinterpret_cast<const uint32_t*>(&x[r][c][0]);
                            uint32_t u[8];
#pragma unroll
                            for (int j = 0; j < 8; j++) u[j] = hmul2(pv[j], vv[j]);
                            uint4 ev, od;
                            ev.x = __byte_perm(u[0], u[1], 0x5410); ev.y = __byte_perm(u[2], u[3], 0x5410);
                            ev.z = __byte_perm(u[4], u[5], 0x5410); ev.w = __byte_perm(u[6], u[7], 0x5410);
                            od.x = __byte_perm(u[0], u[1], 0x7632); od.y = __byte_perm(u[2], u[3], 0x7632);
                            od.z = __byte_perm(u[4], u[5], 0x7632); od.w = __byte_perm(u[6], u[7], 0x7632);
                            if (ok) {
                                uint4* o = reinterpret_cast<uint4*>(row + c * 128);
                                o[0] = ev; o[1] = od;
                            }
                        }
                    }
                }
            }
        }
    } else {
        const int ptid = tid - 32 * P1_WARPS;
        const int posbytes = N * 6;
        if (ptid == 0) {
            asm volatile("mbarrier.init.shared::cta.b64 [%0], 1;" ::"r"(bar));
            asm volatile("fence.mbarrier_init.release.cluster;" ::: "memory");
            asm volatile("mbarrier.arrive.expect_tx.shared::cta.b64 _, [%0], %1;" ::"r"(bar), "r"(posbytes) : "memory");
            asm volatile("cp.async.bulk.shared::cluster.global.mbarrier::complete_tx::bytes [%0], [%1], %2, [%3];"
                         ::"r"(smem_u32(smem + PS_POS)), "l"(pos), "r"(posbytes), "r"(bar) : "memory");
        }
        const int npairs = E >> 1;
        const int gthreads = gridDim.x * P3_THREADS;
        const int gtid = blockIdx.x * P3_THREADS + ptid;
        int2 es[P3_ITERS], ed[P3_ITERS];
#pragma unroll
        for (int it = 0; it < P3_ITERS; it++) {
            const int p = gtid + it * gthreads;
            if (p < npairs) {
                es[it] = __ldcs(reinterpret_cast<const int2*>(src) + p);
                ed[it] = __ldcs(reinterpret_cast<const int2*>(dst) + p);
            }
        }
        if (gtid < NTAB * NRBF) {
            const int di = gtid >> 4, k = gtid & 15;
            const float d = __uint_as_float((uint32_t)(DBASE + di) << 16);
            const float arg = bf16r(d * __bfloat162float(freqs[k]));
            const float s = bf16r(sinf(arg));
            g_G[gtid] = __float2bfloat16_rn(s / d);
        }
        asm volatile("bar.sync 2, %0;" ::"n"(P3_THREADS) : "memory");
        {
            uint32_t done = 0;
            for (int spin = 0; spin < (1 << 22) && !done; spin++) {
                asm volatile("{\n.reg .pred p;\nmbarrier.try_wait.parity.shared::cta.b64 p, [%1], 0;\nselp.u32 %0, 1, 0, p;\n}\n"
                             : "=r"(done) : "r"(bar) : "memory");
            }
        }
        const uint32_t* pw = reinterpret_cast<const uint32_t*>(smem + PS_POS);
        auto loadpos = [&](int n, float& px, float& py, float& pz) {
            const int w = (n * 3) >> 1;
            const uint32_t a = pw[w], b = pw[w + 1];
            if (n & 1) {
                px = __uint_as_float(a & 0xffff0000u); py = __uint_as_float(b << 16); pz = __uint_as_float(b & 0xffff0000u);
            } else {
                px = __uint_as_float(a << 16); py = __uint_as_float(a & 0xffff0000u); pz = __uint_as_float(b << 16);
            }
        };
        uint4 rec[P3_ITERS * 2];
        int slot[P3_ITERS * 2];
#pragma unroll
        for (int q = 0; q < P3_ITERS * 2; q++) {
            const int it = q >> 1;
            slot[q] = -1;
            if (gtid + it * gthreads < npairs) {
                const int s = (q & 1) ? es[it].y : es[it].x;
                const int dd = (q & 1) ? ed[it].y : ed[it].x;
                float sx, sy, sz, tx, ty, tz;
                loadpos(s, sx, sy, sz);
                loadpos(dd, tx, ty, tz);
                const float rx = bf16r(sx - tx), ry = bf16r(sy - ty), rz = bf16r(sz - tz);
                const float sum = bf16r(bf16r(rx * rx) + bf16r(ry * ry) + bf16r(rz * rz));
                const float d = bf16r(__fsqrt_rn(bf16r(sum + 1e-8f)));
                if (d < 5.0f) {
                    const float ca = bf16r(__fdiv_rn(bf16r(3.14159265358979f * d), 5.0f));
                    const float fc = bf16r(0.5f * bf16r(bf16r(__cosf(ca)) + 1.0f));
                    if (fc != 0.0f) {
                        int di = (int)(__float_as_uint(d) >> 16) - DBASE;
                        di = max(di, 0);
                        rec[q].x = (uint32_t)s;
                        rec[q].y = (uint32_t)di | ((uint32_t)dd << 11);
                        rec[q].z = pack_bf16(fc, __fdiv_rn(rx, d));
                        rec[q].w = pack_bf16(__fdiv_rn(ry, d), __fdiv_rn(rz, d));
                        slot[q] = atomicAdd(&g_cnt[(dd >> 3) * CNT_STRIDE], 1);
                    }
                }
            }
        }
#pragma unroll
        for (int q = 0; q < P3_ITERS * 2; q++) {
            if (slot[q] >= 0) {
                if (slot[q] < CAP) {
                    g_rec[(size_t)(rec[q].y >> 14) * CAP + slot[q]] = rec[q];
                } else {
                    g_ovf[atomicAdd(&g_ovf_cnt, 1)] = rec[q];
                }
            }
        }
    }
}

constexpr int M_WARPS = 10;
constexpr int STAGE_ROWS = 16 * ROWB;
constexpr int STAGE_BYTES = STAGE_ROWS + 512 + 256;
constexpr int WARP_BYTES = 2 * STAGE_BYTES + 256;
constexpr int M_SMEM = M_WARPS * WARP_BYTES;

__global__ void __launch_bounds__(M_WARPS * 32, 1)
main_kernel(const __nv_bfloat16* __restrict__ sv, const __nv_bfloat16* __restrict__ wrbf,
            __nv_bfloat16* __restrict__ out, int N) {
    extern __shared__ __align__(128) unsigned char smem[];
    const int warp = threadIdx.x >> 5, lane = threadIdx.x & 31;
    const int g = lane >> 2, t = lane & 3;
    const int ngroups = (N + GRP - 1) / GRP;
    const int group = warp * gridDim.x + blockIdx.x;

    uint32_t wa[3][4][4];
    {
        const unsigned short* w = reinterpret_cast<const unsigned short*>(wrbf);
#pragma unroll
        for (int p = 0; p < 3; p++)
#pragma unroll
            for (int mt = 0; mt < 4; mt++) {
                const int c = p * 64 + 16 * mt + 2 * g;
#pragma unroll
                for (int kh = 0; kh < 2; kh++) {
                    const uint32_t lo = __ldg(reinterpret_cast<const uint32_t*>(w + (2 * t + 8 * kh) * 192 + c));
                    const uint32_t hi = __ldg(reinterpret_cast<const uint32_t*>(w + (2 * t + 8 * kh + 1) * 192 + c));
                    wa[p][mt][2 * kh + 0] = __byte_perm(lo, hi, 0x5410);
                    wa[p][mt][2 * kh + 1] = __byte_perm(lo, hi, 0x7632);
                }
            }
    }
    asm volatile("griddepcontrol.wait;" ::: "memory");
    if (blockIdx.x == 0 && threadIdx.x == 0) g_ovf_cnt = 0;
    if (group >= ngroups) return;

    const uint4* recs = g_rec + (size_t)group * CAP;
    uint4 rnext = __ldcg(recs + (lane & 15));
    const int cnt = __ldcg(&g_cnt[group * CNT_STRIDE]);
    __syncwarp();
    if (lane == 0) g_cnt[group * CNT_STRIDE] = 0;
    const int nsteps = (cnt + 15) >> 4;

    unsigned char* wbase = smem + warp * WARP_BYTES;
    const uint32_t sbase = smem_u32(wbase);
    int ovf_pos = 0;

    auto fetch = [&](int i) -> uint4 {
        if (i < CAP / 16) return __ldcg(recs + i * 16 + (lane & 15));
        const int want = min(16, cnt - i * 16);
        uint4* buf = reinterpret_cast<uint4*>(wbase + 2 * STAGE_BYTES);
        int have = 0;
        while (have < want && ovf_pos < MAXE) {
            uint4 r = make_uint4(0, 0xffffffffu, 0, 0);
            if (ovf_pos + lane < MAXE) r = __ldcg(g_ovf + ovf_pos + lane);
            const bool m = (int)(r.y >> 14) == group;
            const uint32_t bal = __ballot_sync(0xffffffffu, m);
            const int rank = __popc(bal & ((1u << lane) - 1));
            const int room = want - have;
            if (m && rank < room) buf[have + rank] = r;
            const int tot = __popc(bal);
            if (tot > room) {
                ovf_pos += __fns(bal, 0, room + 1);
                have = want;
            } else {
                ovf_pos += 32;
                have += tot;
            }
        }
        __syncwarp();
        uint4 r = buf[lane & 15];
        __syncwarp();
        return r;
    };

    auto issue = [&](int i, uint4 r) {
        if (i < nsteps) {
            const uint32_t st = sbase + (i & 1) * STAGE_BYTES;
            const bool valid = i * 16 + (lane & 15) < cnt;
            if (!valid) r = make_uint4(0, 0, 0, 0);
            if (lane < 16) asm volatile("st.shared.v4.u32 [%0], {%1,%2,%3,%4};" ::"r"(st + STAGE_ROWS + 512 + lane * 16), "r"(r.x), "r"(r.y), "r"(r.z), "r"(r.w) : "memory");
            const int srcv = valid ? (int)r.x : -1;
#pragma unroll
            for (int q = 0; q < 4; q++) {
                const int row = q * 4 + (lane >> 3);
                const int s = __shfl_sync(0xffffffffu, srcv, row);
                const unsigned char* gp = g_tab + (size_t)max(s, 0) * ROWB + (lane & 7) * 16;
                const uint32_t dp = st + row * ROWB + (((lane & 7) ^ (row & 7)) << 4);
                const int sz = s >= 0 ? 16 : 0;
#pragma unroll
                for (int c = 0; c < 5; c++)
                    asm volatile("cp.async.cg.shared.global [%0], [%1], 16, %2;" ::"r"(dp + c * 128), "l"(gp + c * 128), "r"(sz) : "memory");
            }
            {
                const int row = lane >> 1, half = lane & 1;
                const int dv = __shfl_sync(0xffffffffu, valid ? (int)(r.y & 2047u) : -1, row);
                const unsigned char* gp = reinterpret_cast<const unsigned char*>(g_G) + max(dv, 0) * 32 + half * 16;
                const uint32_t dp = st + STAGE_ROWS + row * 32 + ((half ^ ((row >> 2) & 1)) << 4);
                const int sz = dv >= 0 ? 16 : 0;
                asm volatile("cp.async.ca.shared.global [%0], [%1], 16, %2;" ::"r"(dp), "l"(gp), "r"(sz) : "memory");
            }
        }
        asm volatile("cp.async.commit_group;" ::: "memory");
    };

    float acc[4][4][4];
#pragma unroll
    for (int c = 0; c < 4; c++)
#pragma unroll
        for (int mt = 0; mt < 4; mt++)
#pragma unroll
            for (int e = 0; e < 4; e++) acc[c][mt][e] = 0.f;

    issue(0, rnext);
    if (nsteps > 1) rnext = fetch(1);

    const int erow = (lane & 7) + 8 * (lane >> 4);
    const int ehalf = (lane >> 3) & 1;
    for (int i = 0; i < nsteps; i++) {
        issue(i + 1, rnext);
        if (i + 2 < nsteps) rnext = fetch(i + 2);
        asm volatile("cp.async.wait_group 1;" ::: "memory");
        __syncwarp();
        const uint32_t st = sbase + (i & 1) * STAGE_BYTES;
        uint32_t gb[4];
        ldsm4(gb, st + STAGE_ROWS + erow * 32 + ((ehalf ^ ((erow >> 2) & 1)) << 4));
        uint32_t sb[2], rr[3][2];
#pragma unroll
        for (int h = 0; h < 2; h++) {
            uint4 r0, r1;
            const uint32_t ra = st + STAGE_ROWS + 512 + (2 * t + 8 * h) * 16;
            asm volatile("ld.shared.v4.u32 {%0,%1,%2,%3}, [%4];" : "=r"(r0.x), "=r"(r0.y), "=r"(r0.z), "=r"(r0.w) : "r"(ra));
            asm volatile("ld.shared.v4.u32 {%0,%1,%2,%3}, [%4];" : "=r"(r1.x), "=r"(r1.y), "=r"(r1.z), "=r"(r1.w) : "r"(ra + 16));
            const uint32_t f0 = (((r0.y >> 11) & 7u) == (uint32_t)g) ? r0.z : 0u;
            const uint32_t f1 = (((r1.y >> 11) & 7u) == (uint32_t)g) ? r1.z : 0u;
            sb[h] = __byte_perm(f0, f1, 0x5410);
            rr[0][h] = __byte_perm(r0.z, r1.z, 0x7632);
            rr[1][h] = __byte_perm(r0.w, r1.w, 0x5410);
            rr[2][h] = __byte_perm(r0.w, r1.w, 0x7632);
        }
        const uint32_t xaddr = st + erow * ROWB;
#pragma unroll
        for (int mt = 0; mt < 4; mt++) {
            uint32_t wf[3][4];
#pragma unroll
            for (int p = 0; p < 3; p++) {
                float c0[4], c1[4];
                mma16816_z(c0, wa[p][mt][0], wa[p][mt][1], wa[p][mt][2], wa[p][mt][3], gb[0], gb[1]);
                mma16816_z(c1, wa[p][mt][0], wa[p][mt][1], wa[p][mt][2], wa[p][mt][3], gb[2], gb[3]);
                wf[p][0] = pack_bf16(c0[0], c0[1]); wf[p][1] = pack_bf16(c0[2], c0[3]);
                wf[p][2] = pack_bf16(c1[0], c1[1]); wf[p][3] = pack_bf16(c1[2], c1[3]);
            }
            const uint32_t xa = xaddr + (((2 * mt + ehalf) ^ (erow & 7)) << 4);
            uint32_t x[4], mvr[4];
            ldsm4t(x, xa);
            mma16816(acc[0][mt], hmul2(x[0], wf[0][0]), hmul2(x[1], wf[0][1]), hmul2(x[2], wf[0][2]), hmul2(x[3], wf[0][3]), sb[0], sb[1]);
            ldsm4t(x, xa + 4 * 128);
#pragma unroll
            for (int e = 0; e < 4; e++) mvr[e] = hmul2(x[e], wf[2][e]);
#pragma unroll
            for (int j = 0; j < 3; j++) {
                ldsm4t(x, xa + (j + 1) * 128);
                uint32_t m[4];
#pragma unroll
                for (int e = 0; e < 4; e++) m[e] = hfma2(mvr[e], rr[j][e >> 1], hmul2(x[e], wf[1][e]));
                mma16816(acc[j + 1][mt], m[0], m[1], m[2], m[3], sb[0], sb[1]);
            }
        }
        __syncwarp();
    }

#pragma unroll
    for (int b = 0; b < 2; b++) {
        const int node = group * GRP + 2 * t + b;
        if (node < N) {
            const uint32_t* ip = reinterpret_cast<const uint32_t*>(sv + (size_t)node * 256) + g;
            uint32_t* op = reinterpret_cast<uint32_t*>(out + (size_t)node * 256) + g;
            uint32_t v[16];
#pragma unroll
            for (int q = 0; q < 16; q++) v[q] = __ldg(ip + q * 8);
#pragma unroll
            for (int c = 0; c < 4; c++)
#pragma unroll
                for (int mt = 0; mt < 4; mt++) {
                    const uint32_t w = v[c * 4 + mt];
                    const float lo = __uint_as_float(w << 16) + bf16r(acc[c][mt][b]);
                    const float hi = __uint_as_float(w & 0xffff0000u) + bf16r(acc[c][mt][2 + b]);
                    op[(c * 4 + mt) * 8] = pack_bf16(lo, hi);
                }
        }
    }
}

}

extern "C" void kernel_launch(void* const* d_in, const int* in_sizes, int n_in, void* d_out, int out_size) {
    const __nv_bfloat16* sv = (const __nv_bfloat16*)d_in[0];
    const __nv_bfloat16* pos = (const __nv_bfloat16*)d_in[1];
    const int* src = (const int*)d_in[2];
    const int* dst = (const int*)d_in[3];
    const __nv_bfloat16* freqs = (const __nv_bfloat16*)d_in[4];
    const __nv_bfloat16* w1 = (const __nv_bfloat16*)d_in[5];
    const __nv_bfloat16* w2 = (const __nv_bfloat16*)d_in[6];
    const __nv_bfloat16* wrbf = (const __nv_bfloat16*)d_in[7];
    __nv_bfloat16* out = (__nv_bfloat16*)d_out;
    const int N = in_sizes[1] / 3;
    const int E = in_sizes[2];

    static bool init = false;
    if (!init) {
        cudaFuncSetAttribute(prep_kernel, cudaFuncAttributeMaxDynamicSharedMemorySize, PS_TOTAL);
        cudaFuncSetAttribute(main_kernel, cudaFuncAttributeMaxDynamicSharedMemorySize, M_SMEM);
        init = true;
    }
    cudaStream_t stream = cudaStreamPerThread;
    prep_kernel<<<132, P_THREADS, PS_TOTAL, stream>>>(sv, pos, src, dst, freqs, w1, w2, N, E);

    cudaLaunchConfig_t cfg = {};
    cfg.gridDim = dim3(132);
    cfg.blockDim = dim3(M_WARPS * 32);
    cfg.dynamicSmemBytes = M_SMEM;
    cfg.stream = stream;
    cudaLaunchAttribute at[1];
    at[0].id = cudaLaunchAttributeProgrammaticStreamSerialization;
    at[0].val.programmaticStreamSerializationAllowed = 1;
    cfg.attrs = at;
    cfg.numAttrs = 1;
    cudaLaunchKernelEx(&cfg, main_kernel, sv, wrbf, out, N);
}
```

```cpp
#include <cuda_runtime.h>
#include <cuda_bf16.h>
#include <stdint.h>

namespace {

constexpr int D = 64;
constexpr int NRBF = 16;
constexpr int MAXN = 10000;
constexpr int MAXE = 640000;
constexpr int NCTA = 132;
constexpr int GRP = 8;
constexpr int MAXG = (MAXN + GRP - 1) / GRP;
constexpr int CH = 4864;
constexpr int DBASE = 0x38C0;
constexpr int DEND = 0x40A0;
constexpr int NTAB = DEND - DBASE;
constexpr int ROWB = 512;

__device__ __align__(128) unsigned char g_tab[(size_t)(MAXN + 16) * ROWB];
__device__ __align__(128) __nv_bfloat16 g_G[NTAB * NRBF];
__device__ __align__(128) uint2 g_rec[NCTA * CH];
__device__ __align__(128) unsigned short g_pfx[NCTA * NCTA * 16];

__device__ __forceinline__ uint32_t smem_u32(const void* p) { return (uint32_t)__cvta_generic_to_shared(p); }
__device__ __forceinline__ uint32_t pack_bf16(float lo, float hi) {
    uint32_t r;
    asm("cvt.rn.bf16x2.f32 %0, %1, %2;" : "=r"(r) : "f"(hi), "f"(lo));
    return r;
}
__device__ __forceinline__ float bf16r(float x) { return __uint_as_float(pack_bf16(0.f, x) & 0xffff0000u); }
__device__ __forceinline__ uint32_t hmul2(uint32_t a, uint32_t b) {
    uint32_t r;
    asm("mul.rn.bf16x2 %0, %1, %2;" : "=r"(r) : "r"(a), "r"(b));
    return r;
}
__device__ __forceinline__ uint32_t hsub2(uint32_t a, uint32_t b) {
    uint32_t r;
    asm("sub.rn.bf16x2 %0, %1, %2;" : "=r"(r) : "r"(a), "r"(b));
    return r;
}
__device__ __forceinline__ uint32_t hfma2(uint32_t a, uint32_t b, uint32_t c) {
    uint32_t r;
    asm("fma.rn.bf16x2 %0, %1, %2, %3;" : "=r"(r) : "r"(a), "r"(b), "r"(c));
    return r;
}
__device__ __forceinline__ void mma16816(float (&c)[4], const uint32_t (&a)[4], uint32_t b0, uint32_t b1) {
    asm volatile("mma.sync.aligned.m16n8k16.row.col.f32.bf16.bf16.f32 {%0,%1,%2,%3}, {%4,%5,%6,%7}, {%8,%9}, {%0,%1,%2,%3};"
                 : "+f"(c[0]), "+f"(c[1]), "+f"(c[2]), "+f"(c[3])
                 : "r"(a[0]), "r"(a[1]), "r"(a[2]), "r"(a[3]), "r"(b0), "r"(b1));
}
__device__ __forceinline__ void mma16816_z(float (&c)[4], const uint32_t (&a)[4], uint32_t b0, uint32_t b1) {
    asm volatile("mma.sync.aligned.m16n8k16.row.col.f32.bf16.bf16.f32 {%0,%1,%2,%3}, {%4,%5,%6,%7}, {%8,%9}, {%10,%10,%10,%10};"
                 : "=f"(c[0]), "=f"(c[1]), "=f"(c[2]), "=f"(c[3])
                 : "r"(a[0]), "r"(a[1]), "r"(a[2]), "r"(a[3]), "r"(b0), "r"(b1), "f"(0.f));
}
__device__ __forceinline__ void ldsm4(uint32_t (&r)[4], uint32_t addr) {
    asm volatile("ldmatrix.sync.aligned.m8n8.x4.shared.b16 {%0,%1,%2,%3}, [%4];"
                 : "=r"(r[0]), "=r"(r[1]), "=r"(r[2]), "=r"(r[3]) : "r"(addr));
}
__device__ __forceinline__ void ldsm4t(uint32_t (&r)[4], uint32_t addr) {
    asm volatile("ldmatrix.sync.aligned.m8n8.x4.trans.shared.b16 {%0,%1,%2,%3}, [%4];"
                 : "=r"(r[0]), "=r"(r[1]), "=r"(r[2]), "=r"(r[3]) : "r"(addr));
}
__device__ __forceinline__ void mbar_init(uint32_t bar, int cnt) {
    asm volatile("mbarrier.init.shared::cta.b64 [%0], %1;" ::"r"(bar), "r"(cnt) : "memory");
}
__device__ __forceinline__ void mbar_arrive(uint32_t bar) {
    asm volatile("mbarrier.arrive.shared::cta.b64 _, [%0];" ::"r"(bar) : "memory");
}
__device__ __forceinline__ void mbar_expect_tx(uint32_t bar, uint32_t bytes) {
    asm volatile("mbarrier.arrive.expect_tx.shared::cta.b64 _, [%0], %1;" ::"r"(bar), "r"(bytes) : "memory");
}
__device__ __forceinline__ void mbar_wait(uint32_t bar, uint32_t parity) {
    uint32_t done = 0;
    for (int spin = 0; spin < (1 << 20) && !done; spin++) {
        asm volatile("{\n.reg .pred p;\nmbarrier.try_wait.parity.shared::cta.b64 p, [%1], %2;\nselp.u32 %0, 1, 0, p;\n}\n"
                     : "=r"(done) : "r"(bar), "r"(parity) : "memory");
    }
    if (!done) __trap();
}
__device__ __forceinline__ void bulk_g2s(uint32_t dst, const void* src, uint32_t bytes, uint32_t bar) {
    asm volatile("cp.async.bulk.shared::cluster.global.mbarrier::complete_tx::bytes [%0], [%1], %2, [%3];"
                 ::"r"(dst), "l"(src), "r"(bytes), "r"(bar) : "memory");
}
__device__ __forceinline__ void bulk_s2g(void* dst, uint32_t src, uint32_t bytes) {
    asm volatile("cp.async.bulk.global.shared::cta.bulk_group [%0], [%1], %2;" ::"l"(dst), "r"(src), "r"(bytes) : "memory");
}
__device__ __forceinline__ int group_begin(int c, int ngroups) { return (c * ngroups) / NCTA; }

constexpr int P_THREADS = 1024;
constexpr int P1_WARPS = 5;
constexpr int P3_THREADS = P_THREADS - 32 * P1_WARPS;
constexpr int P3_ITERS = 3;
constexpr int W_PITCH = 144;
constexpr int PS_TILE = 0;
constexpr int PS_REC = PS_TILE + P1_WARPS * 8192;
constexpr int PS_PFX = PS_REC + CH * 8;
constexpr int PS_POS = PS_PFX + NCTA * 32;
constexpr int PS_W1 = PS_POS + 60032;
constexpr int PS_W2 = PS_W1 + 64 * W_PITCH;
constexpr int PS_HIST = PS_W2 + 64 * W_PITCH;
constexpr int PS_BAR = PS_HIST + (1280 + 32) * 4;
constexpr int PS_TOTAL = PS_BAR + 64;

__global__ void __launch_bounds__(P_THREADS, 1)
prep_kernel(const __nv_bfloat16* __restrict__ sv, const __nv_bfloat16* __restrict__ pos,
            const int* __restrict__ src, const int* __restrict__ dst,
            const __nv_bfloat16* __restrict__ freqs, const __nv_bfloat16* __restrict__ w1,
            const __nv_bfloat16* __restrict__ w2, int N, int E) {
    extern __shared__ __align__(128) unsigned char smem[];
    const int tid = threadIdx.x, warp = tid >> 5, lane = tid & 31;
    asm volatile("griddepcontrol.launch_dependents;");

    if (warp < P1_WARPS) {
        const int g = lane >> 2, t = lane & 3;
        const int tile = warp * gridDim.x + blockIdx.x;
        const int nrows = min(16, N - tile * 16);
        const uint32_t bar = smem_u32(smem + PS_BAR + 8 + 8 * warp);
        unsigned char* tb = smem + PS_TILE + warp * 8192;
        if (nrows > 0 && lane == 0) {
            mbar_init(bar, 1);
            asm volatile("fence.mbarrier_init.release.cluster;" ::: "memory");
            mbar_expect_tx(bar, nrows * 512);
            bulk_g2s(smem_u32(tb), sv + (size_t)tile * 16 * 256, nrows * 512, bar);
        }
        for (int i = tid; i < 64 * 8; i += 32 * P1_WARPS) {
            const int r = i >> 3, c = i & 7;
            *reinterpret_cast<uint4*>(smem + PS_W1 + r * W_PITCH + c * 16) =
                __ldg(reinterpret_cast<const uint4*>(w1 + r * 64) + c);
            const uint4 v = __ldg(reinterpret_cast<const uint4*>(w2 + r * 192 + 64) + c);
            const int tt = c >> 1, j0 = (c & 1) * 4;
            uint32_t* o = reinterpret_cast<uint32_t*>(smem + PS_W2 + r * W_PITCH);
            o[4 * (j0 + 0) + tt] = v.x; o[4 * (j0 + 1) + tt] = v.y;
            o[4 * (j0 + 2) + tt] = v.z; o[4 * (j0 + 3) + tt] = v.w;
        }
        asm volatile("bar.sync 1, %0;" ::"n"(32 * P1_WARPS) : "memory");
        if (nrows > 0) {
            mbar_wait(bar, 0);
            uint4* r0 = reinterpret_cast<uint4*>(tb + g * 512 + t * 32);
            uint4* r1 = reinterpret_cast<uint4*>(tb + (g + 8) * 512 + t * 32);
            uint32_t h[4][4];
            {
                uint4 xa[2] = {r0[0], r0[1]}, xb[2] = {r1[0], r1[1]};
                const uint32_t* s0 = reinterpret_cast<const uint32_t*>(xa);
                const uint32_t* s1 = reinterpret_cast<const uint32_t*>(xb);
                float a[8][4];
                const int i = lane & 7, hi = (lane >> 3) & 1, nsel = lane >> 4;
#pragma unroll
                for (int q = 0; q < 4; q++) {
                    const int krow = 16 * (i >> 1) + 4 * q + (i & 1) + 2 * hi;
                    const uint32_t af[4] = {s0[2 * q], s1[2 * q], s0[2 * q + 1], s1[2 * q + 1]};
#pragma unroll
                    for (int jp = 0; jp < 4; jp++) {
                        uint32_t b[4];
                        ldsm4t(b, smem_u32(smem + PS_W1 + krow * W_PITCH + (2 * jp + nsel) * 16));
                        if (q == 0) {
                            mma16816_z(a[2 * jp], af, b[0], b[1]);
                            mma16816_z(a[2 * jp + 1], af, b[2], b[3]);
                        } else {
                            mma16816(a[2 * jp], af, b[0], b[1]);
                            mma16816(a[2 * jp + 1], af, b[2], b[3]);
                        }
                    }
                }
#pragma unroll
                for (int j = 0; j < 8; j++) {
                    float f[4];
#pragma unroll
                    for (int e = 0; e < 4; e++) {
                        const float z = bf16r(a[j][e]);
                        f[e] = __fdividef(z, 1.0f + __expf(-z));
                    }
                    h[j >> 1][(j & 1) * 2 + 0] = pack_bf16(f[0], f[1]);
                    h[j >> 1][(j & 1) * 2 + 1] = pack_bf16(f[2], f[3]);
                }
            }
            r0[0] = make_uint4(h[0][0], h[0][2], h[1][0], h[1][2]);
            r0[1] = make_uint4(h[2][0], h[2][2], h[3][0], h[3][2]);
            r1[0] = make_uint4(h[0][1], h[0][3], h[1][1], h[1][3]);
            r1[1] = make_uint4(h[2][1], h[2][3], h[3][1], h[3][3]);
            float p[8][4];
            {
                const int i = lane & 15, nsel = lane >> 4;
#pragma unroll
                for (int q = 0; q < 4; q++) {
#pragma unroll
                    for (int jp = 0; jp < 4; jp++) {
                        uint32_t b[4];
                        ldsm4t(b, smem_u32(smem + PS_W2 + (16 * q + i) * W_PITCH + (2 * jp + nsel) * 16));
                        if (q == 0) {
                            mma16816_z(p[2 * jp], h[0], b[0], b[1]);
                            mma16816_z(p[2 * jp + 1], h[0], b[2], b[3]);
                        } else {
                            mma16816(p[2 * jp], h[q], b[0], b[1]);
                            mma16816(p[2 * jp + 1], h[q], b[2], b[3]);
                        }
                    }
                }
            }
#pragma unroll
            for (int r = 0; r < 2; r++) {
                uint4* row = r ? r1 : r0;
                uint32_t pv[8];
#pragma unroll
                for (int j = 0; j < 8; j++) pv[j] = pack_bf16(p[j][2 * r], p[j][2 * r + 1]);
#pragma unroll
                for (int c = 1; c < 4; c++) {
                    uint4 vx[2] = {row[c * 8], row[c * 8 + 1]};
                    const uint32_t* vv = reinterpret_cast<const uint32_t*>(vx);
                    uint32_t u[8];
#pragma unroll
                    for (int j = 0; j < 8; j++) u[j] = hmul2(pv[j], vv[j]);
                    row[c * 8] = make_uint4(__byte_perm(u[0], u[1], 0x5410), __byte_perm(u[2], u[3], 0x5410),
                                            __byte_perm(u[4], u[5], 0x5410), __byte_perm(u[6], u[7], 0x5410));
                    row[c * 8 + 1] = make_uint4(__byte_perm(u[0], u[1], 0x7632), __byte_perm(u[2], u[3], 0x7632),
                                                __byte_perm(u[4], u[5], 0x7632), __byte_perm(u[6], u[7], 0x7632));
                }
            }
            asm volatile("fence.proxy.async.shared::cta;" ::: "memory");
            __syncwarp();
            if (lane == 0) {
                bulk_s2g(g_tab + (size_t)tile * 16 * ROWB, smem_u32(tb), nrows * 512);
                asm volatile("cp.async.bulk.commit_group;" ::: "memory");
                asm volatile("cp.async.bulk.wait_group 0;" ::: "memory");
            }
        }
    } else {
        const int ptid = tid - 32 * P1_WARPS, pwarp = warp - P1_WARPS;
        const uint32_t bar = smem_u32(smem + PS_BAR);
        const int posbytes = N * 6;
        if (ptid == 0) {
            mbar_init(bar, 1);
            asm volatile("fence.mbarrier_init.release.cluster;" ::: "memory");
            mbar_expect_tx(bar, posbytes);
            bulk_g2s(smem_u32(smem + PS_POS), pos, posbytes, bar);
        }
        const int npairs = E >> 1;
        const int ppc = (npairs + NCTA - 1) / NCTA;
        const int pbeg = blockIdx.x * ppc, pend = min(pbeg + ppc, npairs);
        int2 es[P3_ITERS], ed[P3_ITERS];
#pragma unroll
        for (int it = 0; it < P3_ITERS; it++) {
            const int p = pbeg + ptid + it * P3_THREADS;
            if (p < pend) {
                es[it] = __ldcs(reinterpret_cast<const int2*>(src) + p);
                ed[it] = __ldcs(reinterpret_cast<const int2*>(dst) + p);
            }
        }
        int* hist = reinterpret_cast<int*>(smem + PS_HIST);
        for (int i = ptid; i < 1280; i += P3_THREADS) hist[i] = 0;
        {
            const int gi = ptid * NCTA + blockIdx.x;
            if (gi < NTAB * NRBF) {
                const int di = gi >> 4, k = gi & 15;
                const float d = __uint_as_float((uint32_t)(DBASE + di) << 16);
                const float arg = bf16r(d * __bfloat162float(freqs[k]));
                const float s = bf16r(sinf(arg));
                g_G[gi] = __float2bfloat16_rn(s / d);
            }
        }
        asm volatile("bar.sync 2, %0;" ::"n"(P3_THREADS) : "memory");
        mbar_wait(bar, 0);
        const uint32_t* pw = reinterpret_cast<const uint32_t*>(smem + PS_POS);
        uint2 rec[P3_ITERS * 2];
        int key[P3_ITERS * 2];
#pragma unroll
        for (int q = 0; q < P3_ITERS * 2; q++) {
            const int it = q >> 1;
            key[q] = -1;
            if (pbeg + ptid + it * P3_THREADS < pend) {
                const int s = (q & 1) ? es[it].y : es[it].x;
                const int dd = (q & 1) ? ed[it].y : ed[it].x;
                const int ws = (s * 3) >> 1, wd = (dd * 3) >> 1;
                const uint32_t sa = pw[ws], sb = pw[ws + 1], da = pw[wd], db = pw[wd + 1];
                const uint32_t shs = (s & 1) << 4, shd = (dd & 1) << 4;
                const uint32_t rxy = hsub2(__funnelshift_r(sa, sb, shs), __funnelshift_r(da, db, shd));
                const uint32_t rz = hsub2(sb >> shs, db >> shd);
                const uint32_t qxy = hmul2(rxy, rxy), qz = hmul2(rz, rz);
                const float sum = (__uint_as_float(qxy << 16) + __uint_as_float(qxy & 0xffff0000u)) + __uint_as_float(qz << 16);
                if (sum < 23.9375f) {
                    const uint32_t exy = hmul2(rxy, 0x3e803e80u), ez = hmul2(rz, 0x3e803e80u);
                    rec[q].x = exy | ((dd & 1) << 14) | ((dd & 2) << 29);
                    rec[q].y = (ez & 0xffffu) | ((dd & 4) << 12) | ((uint32_t)s << 16);
                    const int grp = dd >> 3;
                    key[q] = (grp << 13) | atomicAdd(&hist[grp], 1);
                }
            }
        }
        asm volatile("bar.sync 2, %0;" ::"n"(P3_THREADS) : "memory");
        int2 hv = make_int2(0, 0);
        int incl = 0;
        if (pwarp < 20) {
            hv = reinterpret_cast<int2*>(hist)[ptid];
            incl = hv.x + hv.y;
#pragma unroll
            for (int o = 1; o < 32; o <<= 1) {
                const int v = __shfl_up_sync(0xffffffffu, incl, o);
                if (lane >= o) incl += v;
            }
            if (lane == 31) hist[1280 + pwarp] = incl;
        }
        asm volatile("bar.sync 2, %0;" ::"n"(P3_THREADS) : "memory");
        if (pwarp < 20) {
            int wsum = (lane < pwarp) ? hist[1280 + lane] : 0;
            wsum = __reduce_add_sync(0xffffffffu, wsum);
            const int ex = wsum + incl - hv.x - hv.y;
            reinterpret_cast<int2*>(hist)[ptid] = make_int2(ex, ex + hv.x);
        }
        asm volatile("bar.sync 2, %0;" ::"n"(P3_THREADS) : "memory");
        uint2* srec = reinterpret_cast<uint2*>(smem + PS_REC);
#pragma unroll
        for (int q = 0; q < P3_ITERS * 2; q++)
            if (key[q] >= 0) srec[hist[key[q] >> 13] + (key[q] & 8191)] = rec[q];
        const int ngroups = (N + GRP - 1) / GRP;
        unsigned short* spfx = reinterpret_cast<unsigned short*>(smem + PS_PFX);
        for (int i = ptid; i < NCTA * 16; i += P3_THREADS)
            spfx[i] = (unsigned short)hist[min(group_begin(i >> 4, ngroups) + (i & 15), ngroups)];
        asm volatile("fence.proxy.async.shared::cta;" ::: "memory");
        asm volatile("bar.sync 2, %0;" ::"n"(P3_THREADS) : "memory");
        if (ptid == 0) {
            const int total = hist[ngroups];
            const int bytes = ((total + 1) >> 1) * 16;
            if (bytes > 0) bulk_s2g(g_rec + blockIdx.x * CH, smem_u32(srec), bytes);
            bulk_s2g(g_pfx + blockIdx.x * NCTA * 16, smem_u32(spfx), NCTA * 32);
            asm volatile("cp.async.bulk.commit_group;" ::: "memory");
            asm volatile("cp.async.bulk.wait_group 0;" ::: "memory");
        }
    }
}

constexpr int UNITS = 3;
constexpr int STAGES = 3;
constexpr int M_THREADS = UNITS * 160;
constexpr int ST_G = 32 * ROWB;
constexpr int ST_S = ST_G + 1024;
constexpr int ST_R = ST_S + 512;
constexpr int ST_META = ST_R + 192;
constexpr int STAGE_BYTES = ST_R + 256;
constexpr int RCAP = 5632;
constexpr int MAXQ = 10;
constexpr int MS_RAW = UNITS * STAGES * STAGE_BYTES;
constexpr int MS_IDX = MS_RAW + RCAP * 8;
constexpr int MS_PF = MS_IDX + RCAP * 2;
constexpr int MS_PRE = MS_PF + NCTA * 32;
constexpr int MS_DELTA = MS_PRE + MAXQ * 136 * 4;
constexpr int MS_MISC = MS_DELTA + 136 * 4;
constexpr int MS_BAR = MS_MISC + 32 * 4;
constexpr int M_SMEM = MS_BAR + (2 * UNITS * STAGES + 1) * 8;
static_assert(M_SMEM <= 232448, "smem");
static_assert(MS_BAR % 8 == 0, "align");

__global__ void __launch_bounds__(M_THREADS, 1)
main_kernel(const __nv_bfloat16* __restrict__ sv, const __nv_bfloat16* __restrict__ w2,
            const __nv_bfloat16* __restrict__ wrbf, __nv_bfloat16* __restrict__ out, int N) {
    extern __shared__ __align__(128) unsigned char smem[];
    const int tid = threadIdx.x, warp = tid >> 5, lane = tid & 31;
    const int g = lane >> 2, t = lane & 3;
    const int ngroups = (N + GRP - 1) / GRP;
    const int q0 = group_begin(blockIdx.x, ngroups);
    const int nq = group_begin(blockIdx.x + 1, ngroups) - q0;
    const uint32_t sbase = smem_u32(smem);
    const uint32_t rawbar = sbase + MS_BAR + 2 * UNITS * STAGES * 8;
    int* misc = reinterpret_cast<int*>(smem + MS_MISC);
    const bool is_prod = warp >= UNITS * 4;
    const int unit = is_prod ? warp - UNITS * 4 : warp >> 2;
    const int w = warp & 3;

    if (tid == 0) {
        for (int i = 0; i < UNITS * STAGES; i++) {
            mbar_init(sbase + MS_BAR + i * 16, 33);
            mbar_init(sbase + MS_BAR + i * 16 + 8, 4);
        }
        mbar_init(rawbar, 1);
        asm volatile("fence.mbarrier_init.release.cluster;" ::: "memory");
        misc[24] = UNITS;
    }
    uint32_t wa[3][4], pa[2][4][4];
    if (!is_prod) {
        const int c = 16 * w + 2 * g;
#pragma unroll
        for (int p = 0; p < 3; p++)
#pragma unroll
            for (int kh = 0; kh < 2; kh++) {
                const uint32_t lo = __ldg(reinterpret_cast<const uint32_t*>(wrbf + (2 * t + 8 * kh) * 192 + p * 64 + c));
                const uint32_t hi = __ldg(reinterpret_cast<const uint32_t*>(wrbf + (2 * t + 8 * kh + 1) * 192 + p * 64 + c));
                wa[p][2 * kh + 0] = __byte_perm(lo, hi, 0x5410);
                wa[p][2 * kh + 1] = __byte_perm(lo, hi, 0x7632);
            }
#pragma unroll
        for (int p = 0; p < 2; p++)
#pragma unroll
            for (int q = 0; q < 4; q++)
#pragma unroll
                for (int kh = 0; kh < 2; kh++) {
                    const int r = 8 * (t + 4 * kh) + 2 * q;
                    const uint32_t lo = __ldg(reinterpret_cast<const uint32_t*>(w2 + r * 192 + p * 128 + c));
                    const uint32_t hi = __ldg(reinterpret_cast<const uint32_t*>(w2 + (r + 1) * 192 + p * 128 + c));
                    pa[p][q][2 * kh + 0] = __byte_perm(lo, hi, 0x5410);
                    pa[p][q][2 * kh + 1] = __byte_perm(lo, hi, 0x7632);
                }
    }
    asm volatile("griddepcontrol.wait;" ::: "memory");

    unsigned short* pf = reinterpret_cast<unsigned short*>(smem + MS_PF);
    int* delta = reinterpret_cast<int*>(smem + MS_DELTA);
    int a0 = 0, len = 0, incl = 0;
    if (warp < 5) {
        if (tid < NCTA) {
            const uint4* bp = reinterpret_cast<const uint4*>(g_pfx + (tid * NCTA + blockIdx.x) * 16);
            const uint4 b0 = __ldcg(bp), b1 = __ldcg(bp + 1);
            reinterpret_cast<uint4*>(pf)[tid * 2] = b0;
            reinterpret_cast<uint4*>(pf)[tid * 2 + 1] = b1;
            a0 = (b0.x & 0xffffu) & ~1;
            const int wi = nq >> 1;
            uint32_t ew = (wi & 4) ? ((wi & 2) ? ((wi & 1) ? b1.w : b1.z) : ((wi & 1) ? b1.y : b1.x))
                                   : ((wi & 2) ? ((wi & 1) ? b0.w : b0.z) : ((wi & 1) ? b0.y : b0.x));
            const int e = (nq & 1) ? (int)(ew >> 16) : (int)(ew & 0xffffu);
            len = ((e + 1) & ~1) - a0;
        }
        incl = len;
#pragma unroll
        for (int o = 1; o < 32; o <<= 1) {
            const int v = __shfl_up_sync(0xffffffffu, incl, o);
            if (lane >= o) incl += v;
        }
        if (lane == 31) misc[warp] = incl;
    }
    __syncthreads();
    const int rtotal = misc[0] + misc[1] + misc[2] + misc[3] + misc[4];
    const bool fits = rtotal <= RCAP;
    if (tid < NCTA) {
        int off = incl - len;
        for (int i = 0; i < warp; i++) off += misc[i];
        delta[tid] = off - a0;
        if (fits) {
            if (tid == 0) mbar_expect_tx(rawbar, rtotal * 8);
            if (len > 0) bulk_g2s(sbase + MS_RAW + off * 8, g_rec + tid * CH + a0, len * 8, rawbar);
        }
    }
    int cq[5], pre = 0;
    if (warp < nq) {
        int sum = 0;
#pragma unroll
        for (int k = 0; k < 5; k++) {
            const int p = lane * 5 + k;
            cq[k] = p < NCTA ? (int)pf[p * 16 + warp + 1] - (int)pf[p * 16 + warp] : 0;
            sum += cq[k];
        }
        int in2 = sum;
#pragma unroll
        for (int o = 1; o < 32; o <<= 1) {
            const int v = __shfl_up_sync(0xffffffffu, in2, o);
            if (lane >= o) in2 += v;
        }
        pre = in2 - sum;
        if (lane == 31) misc[8 + warp] = in2;
    }
    __syncthreads();
    if (warp < nq) {
        if (fits) {
            int base = (lane < warp) ? misc[8 + lane] : 0;
            base = __reduce_add_sync(0xffffffffu, base) + pre;
            unsigned short* idx = reinterpret_cast<unsigned short*>(smem + MS_IDX);
#pragma unroll
            for (int k = 0; k < 5; k++) {
                const int p = lane * 5 + k;
                if (cq[k] > 0) {
                    const int r = delta[p] + pf[p * 16 + warp];
                    for (int c = 0; c < cq[k]; c++) idx[base + c] = (unsigned short)(r + c);
                    base += cq[k];
                }
            }
        } else {
            int* prq = reinterpret_cast<int*>(smem + MS_PRE) + warp * 136;
#pragma unroll
            for (int k = 0; k < 5; k++) {
                const int p = lane * 5 + k;
                if (p < NCTA) prq[p] = pre;
                pre += cq[k];
            }
        }
    }
    __syncthreads();

    const uint32_t ubase = sbase + unit * STAGES * STAGE_BYTES;
    const uint32_t ubar = sbase + MS_BAR + unit * STAGES * 16;
    if (is_prod) {
        if (fits) mbar_wait(rawbar, 0);
        const uint2* raw = reinterpret_cast<const uint2*>(smem + MS_RAW);
        const unsigned short* idx = reinterpret_cast<const unsigned short*>(smem + MS_IDX);
        int st = 0, ph = 1;
        int q = unit;
        while (q < nq) {
            int base = (lane < q) ? misc[8 + lane] : 0;
            base = __reduce_add_sync(0xffffffffu, base);
            const int cnt = misc[8 + q];
            const int nb = max(1, (cnt + 31) >> 5);
            for (int b = 0; b < nb; b++) {
                const int j = b * 32 + lane;
                const bool valid = j < cnt;
                uint2 r = make_uint2(0, 0);
                if (valid) {
                    if (fits) {
                        r = raw[idx[base + j]];
                    } else {
                        const int* prq = reinterpret_cast<const int*>(smem + MS_PRE) + q * 136;
                        int lo = 0, hi = NCTA;
                        while (hi - lo > 1) {
                            const int mid = (lo + hi) >> 1;
                            if (prq[mid] <= j) lo = mid; else hi = mid;
                        }
                        r = __ldcg(g_rec + lo * CH + pf[lo * 16 + q] + (j - prq[lo]));
                    }
                }
                const uint32_t dl = ((r.x >> 14) & 1u) | ((r.x >> 29) & 2u) | ((r.y >> 12) & 4u);
                const float rx = 4.0f * __uint_as_float((r.x << 16) & 0xbfff0000u);
                const float ry = 4.0f * __uint_as_float(r.x & 0xbfff0000u);
                const float rz = 4.0f * __uint_as_float((r.y << 16) & 0xbfff0000u);
                const float sum = bf16r((bf16r(rx * rx) + bf16r(ry * ry)) + bf16r(rz * rz));
                const float d = bf16r(__fsqrt_rn(bf16r(sum + 1e-8f)));
                const float ca = bf16r(__fdiv_rn(bf16r(3.14159265358979f * d), 5.0f));
                const float fc = valid ? 0.5f * bf16r(bf16r(__cosf(ca)) + 1.0f) : 0.f;
                const int di = min(max((int)(__float_as_uint(d) >> 16) - DBASE, 0), NTAB - 1);
                const uint32_t r01 = pack_bf16(__fdiv_rn(rx, d), __fdiv_rn(ry, d));
                const uint32_t r2f = pack_bf16(__fdiv_rn(rz, d), fc);
                const uint32_t fw = (dl & 1u) ? (r2f & 0xffff0000u) : (r2f >> 16);
                const int srcv = valid ? (int)(r.y >> 16) : -1;

                mbar_wait(ubar + st * 16 + 8, ph);
                const uint32_t sb = ubase + st * STAGE_BYTES;
                asm volatile("st.shared.v4.u32 [%0], {%1,%2,%3,%4};" ::"r"(sb + ST_S + lane * 16),
                             "r"((dl >> 1) == 0 ? fw : 0u), "r"((dl >> 1) == 1 ? fw : 0u),
                             "r"((dl >> 1) == 2 ? fw : 0u), "r"((dl >> 1) == 3 ? fw : 0u) : "memory");
                {
                    const uint32_t ra = sb + ST_R + ((lane >> 1) & 3) * 16 + (lane >> 3) * 4 + (lane & 1) * 2;
                    asm volatile("st.shared.u16 [%0], %1;" ::"r"(ra), "h"((unsigned short)(r01 & 0xffffu)) : "memory");
                    asm volatile("st.shared.u16 [%0], %1;" ::"r"(ra + 64), "h"((unsigned short)(r01 >> 16)) : "memory");
                    asm volatile("st.shared.u16 [%0], %1;" ::"r"(ra + 128), "h"((unsigned short)(r2f & 0xffffu)) : "memory");
                }
                if (lane == 0) {
                    const uint32_t flags = (b == 0 ? 1u : 0u) | (b == nb - 1 ? 2u : 0u) | (cnt - b * 32 > 16 ? 4u : 0u);
                    asm volatile("st.shared.v2.u32 [%0], {%1,%2};" ::"r"(sb + ST_META), "r"(flags), "r"(q0 + q) : "memory");
                }
#pragma unroll
                for (int k = 0; k < 8; k++) {
                    const int e = k * 4 + (lane >> 3);
                    const int s = __shfl_sync(0xffffffffu, srcv, e);
                    const unsigned char* gp = g_tab + (size_t)max(s, 0) * ROWB + (lane & 7) * 16;
                    const uint32_t dp = sb + e * ROWB + (((lane & 7) ^ (e & 7)) << 4);
                    const int sz = s >= 0 ? 16 : 0;
#pragma unroll
                    for (int c = 0; c < 4; c++)
                        asm volatile("cp.async.cg.shared.global [%0], [%1], 16, %2;" ::"r"(dp + c * 128), "l"(gp + c * 128), "r"(sz) : "memory");
                }
                {
                    const unsigned char* gp = reinterpret_cast<const unsigned char*>(g_G) + di * 32;
                    const uint32_t dp = sb + ST_G + lane * 32;
                    const uint32_t x = ((lane >> 2) & 1) << 4;
                    const int sz = valid ? 16 : 0;
                    asm volatile("cp.async.ca.shared.global [%0], [%1], 16, %2;" ::"r"(dp + x), "l"(gp), "r"(sz) : "memory");
                    asm volatile("cp.async.ca.shared.global [%0], [%1], 16, %2;" ::"r"(dp + (x ^ 16u)), "l"(gp + 16), "r"(sz) : "memory");
                }
                asm volatile("cp.async.mbarrier.arrive.noinc.shared::cta.b64 [%0];" ::"r"(ubar + st * 16) : "memory");
                __syncwarp();
                if (lane == 0) mbar_arrive(ubar + st * 16);
                if (++st == STAGES) { st = 0; ph ^= 1; }
            }
            int nx = 0;
            if (lane == 0) nx = atomicAdd(&misc[24], 1);
            q = __shfl_sync(0xffffffffu, nx, 0);
        }
        mbar_wait(ubar + st * 16 + 8, ph);
        if (lane == 0)
            asm volatile("st.shared.v2.u32 [%0], {%1,%2};" ::"r"(ubase + st * STAGE_BYTES + ST_META), "r"(8u), "r"(0) : "memory");
        __syncwarp();
        mbar_arrive(ubar + st * 16);
        if (lane == 0) mbar_arrive(ubar + st * 16);
    } else {
        float acc[4][4];
#pragma unroll
        for (int c = 0; c < 4; c++)
#pragma unroll
            for (int e = 0; e < 4; e++) acc[c][e] = 0.f;
        uint32_t svv[4][2];
        const int erow = (lane & 7) + 8 * (lane >> 4);
        const int ehalf = (lane >> 3) & 1;
        const uint32_t hoff = erow * ROWB;
        const uint32_t sw = (uint32_t)(lane & 7);
        const uint32_t uoff = erow * ROWB + 128 + (((uint32_t)(2 * w + ehalf) ^ sw) << 4);
        const uint32_t goff = ST_G + erow * 32 + ((ehalf ^ ((erow >> 2) & 1)) << 4);
        int st = 0, ph = 0;
        while (true) {
            mbar_wait(ubar + st * 16, ph);
            const uint32_t sb = ubase + st * STAGE_BYTES;
            uint32_t flags, grp;
            asm volatile("ld.shared.v2.u32 {%0,%1}, [%2];" : "=r"(flags), "=r"(grp) : "r"(sb + ST_META));
            if (flags & 8u) break;
            if (flags & 1u) {
#pragma unroll
                for (int b = 0; b < 2; b++) {
                    const int node = min((int)grp * GRP + 2 * t + b, N - 1);
                    const uint32_t* ip = reinterpret_cast<const uint32_t*>(sv + (size_t)node * 256) + 8 * w + g;
#pragma unroll
                    for (int c = 0; c < 4; c++) svv[c][b] = __ldg(ip + c * 32);
                }
            }
            uint32_t sf[4], rr[3][4];
            ldsm4t(sf, sb + ST_S + lane * 16);
#pragma unroll
            for (int j = 0; j < 3; j++)
                asm volatile("ld.shared.v4.u32 {%0,%1,%2,%3}, [%4];" : "=r"(rr[j][0]), "=r"(rr[j][1]), "=r"(rr[j][2]), "=r"(rr[j][3])
                             : "r"(sb + ST_R + j * 64 + t * 16));
#pragma unroll
            for (int s = 0; s < 2; s++) {
                if (s == 0 || (flags & 4u)) {
                    const uint32_t rb = sb + s * 16 * ROWB;
                    float ps[2][4], pv[2][4];
#pragma unroll
                    for (int q = 0; q < 4; q++) {
                        uint32_t hb[4];
                        ldsm4(hb, rb + hoff + (((uint32_t)(2 * q + ehalf) ^ sw) << 4));
                        if (q == 0) {
                            mma16816_z(ps[0], pa[0][0], hb[0], hb[1]); mma16816_z(ps[1], pa[0][0], hb[2], hb[3]);
                            mma16816_z(pv[0], pa[1][0], hb[0], hb[1]); mma16816_z(pv[1], pa[1][0], hb[2], hb[3]);
                        } else {
                            mma16816(ps[0], pa[0][q], hb[0], hb[1]); mma16816(ps[1], pa[0][q], hb[2], hb[3]);
                            mma16816(pv[0], pa[1][q], hb[0], hb[1]); mma16816(pv[1], pa[1][q], hb[2], hb[3]);
                        }
                    }
                    uint32_t gb[4];
                    ldsm4(gb, sb + goff + s * 512);
                    float f0[4], f1[4];
                    uint32_t m[4], mvr[4], wv[4];
                    mma16816_z(f0, wa[1], gb[0], gb[1]); mma16816_z(f1, wa[1], gb[2], gb[3]);
                    wv[0] = pack_bf16(f0[0], f0[1]); wv[1] = pack_bf16(f0[2], f0[3]);
                    wv[2] = pack_bf16(f1[0], f1[1]); wv[3] = pack_bf16(f1[2], f1[3]);
                    mma16816_z(f0, wa[0], gb[0], gb[1]); mma16816_z(f1, wa[0], gb[2], gb[3]);
                    m[0] = pack_bf16(f0[0] * ps[0][0], f0[1] * ps[0][1]); m[1] = pack_bf16(f0[2] * ps[0][2], f0[3] * ps[0][3]);
                    m[2] = pack_bf16(f1[0] * ps[1][0], f1[1] * ps[1][1]); m[3] = pack_bf16(f1[2] * ps[1][2], f1[3] * ps[1][3]);
                    mma16816(acc[0], m, sf[2 * s], sf[2 * s + 1]);
                    mma16816_z(f0, wa[2], gb[0], gb[1]); mma16816_z(f1, wa[2], gb[2], gb[3]);
                    mvr[0] = pack_bf16(f0[0] * pv[0][0], f0[1] * pv[0][1]); mvr[1] = pack_bf16(f0[2] * pv[0][2], f0[3] * pv[0][3]);
                    mvr[2] = pack_bf16(f1[0] * pv[1][0], f1[1] * pv[1][1]); mvr[3] = pack_bf16(f1[2] * pv[1][2], f1[3] * pv[1][3]);
#pragma unroll
                    for (int j = 0; j < 3; j++) {
                        uint32_t x[4];
                        ldsm4t(x, rb + uoff + j * 128);
#pragma unroll
                        for (int e = 0; e < 4; e++) m[e] = hfma2(mvr[e], rr[j][2 * s + (e >> 1)], hmul2(x[e], wv[e]));
                        mma16816(acc[j + 1], m, sf[2 * s], sf[2 * s + 1]);
                    }
                }
            }
            __syncwarp();
            if (lane == 0) mbar_arrive(ubar + st * 16 + 8);
            if (++st == STAGES) { st = 0; ph ^= 1; }
            if (flags & 2u) {
#pragma unroll
                for (int b = 0; b < 2; b++) {
                    const int node = (int)grp * GRP + 2 * t + b;
                    uint32_t* op = reinterpret_cast<uint32_t*>(out + (size_t)node * 256) + 8 * w + g;
#pragma unroll
                    for (int c = 0; c < 4; c++) {
                        const uint32_t v = svv[c][b];
                        const uint32_t o = pack_bf16(__uint_as_float(v << 16) + acc[c][b],
                                                     __uint_as_float(v & 0xffff0000u) + acc[c][2 + b]);
                        if (node < N) op[c * 32] = o;
                    }
                }
#pragma unroll
                for (int c = 0; c < 4; c++)
#pragma unroll
                    for (int e = 0; e < 4; e++) acc[c][e] = 0.f;
            }
        }
    }
}

}

extern "C" void kernel_launch(void* const* d_in, const int* in_sizes, int n_in, void* d_out, int out_size) {
    const __nv_bfloat16* sv = (const __nv_bfloat16*)d_in[0];
    const __nv_bfloat16* pos = (const __nv_bfloat16*)d_in[1];
    const int* src = (const int*)d_in[2];
    const int* dst = (const int*)d_in[3];
    const __nv_bfloat16* freqs = (const __nv_bfloat16*)d_in[4];
    const __nv_bfloat16* w1 = (const __nv_bfloat16*)d_in[5];
    const __nv_bfloat16* w2 = (const __nv_bfloat16*)d_in[6];
    const __nv_bfloat16* wrbf = (const __nv_bfloat16*)d_in[7];
    __nv_bfloat16* out = (__nv_bfloat16*)d_out;
    const int N = in_sizes[1] / 3;
    const int E = in_sizes[2];

    static bool init = false;
    if (!init) {
        cudaFuncSetAttribute(prep_kernel, cudaFuncAttributeMaxDynamicSharedMemorySize, PS_TOTAL);
        cudaFuncSetAttribute(main_kernel, cudaFuncAttributeMaxDynamicSharedMemorySize, M_SMEM);
        init = true;
    }
    cudaStream_t stream = cudaStreamPerThread;
    prep_kernel<<<NCTA, P_THREADS, PS_TOTAL, stream>>>(sv, pos, src, dst, freqs, w1, w2, N, E);

    cudaLaunchConfig_t cfg = {};
    cfg.gridDim = dim3(NCTA);
    cfg.blockDim = dim3(M_THREADS);
    cfg.dynamicSmemBytes = M_SMEM;
    cfg.stream = stream;
    cudaLaunchAttribute at[1];
    at[0].id = cudaLaunchAttributeProgrammaticStreamSerialization;
    at[0].val.programmaticStreamSerializationAllowed = 1;
    cfg.attrs = at;
    cfg.numAttrs = 1;
    cudaLaunchKernelEx(&cfg, main_kernel, sv, w2, wrbf, out, N);
}
```

```cpp
#include <cuda_runtime.h>
#include <cuda_bf16.h>
#include <stdint.h>

namespace {

constexpr int D = 64;
constexpr int NRBF = 16;
constexpr int MAXN = 10000;
constexpr int MAXE = 640000;
constexpr int NCTA = 132;
constexpr int GRP = 8;
constexpr int MAXG = (MAXN + GRP - 1) / GRP;
constexpr int CH = 4864;
constexpr int DBASE = 0x38C0;
constexpr int DEND = 0x40A0;
constexpr int NTAB = DEND - DBASE;
constexpr int ROWB = 512;

__device__ __align__(128) unsigned char g_tab[(size_t)(MAXN + 16) * ROWB];
__device__ __align__(128) __nv_bfloat16 g_G[NTAB * NRBF];
__device__ __align__(128) uint2 g_rec[NCTA * CH];
__device__ __align__(128) unsigned short g_pfx[NCTA * NCTA * 16];

#define STAMP(k) do {} while (0)

__device__ __forceinline__ uint32_t smem_u32(const void* p) { return (uint32_t)__cvta_generic_to_shared(p); }
__device__ __forceinline__ uint32_t pack_bf16(float lo, float hi) {
    uint32_t r;
    asm("cvt.rn.bf16x2.f32 %0, %1, %2;" : "=r"(r) : "f"(hi), "f"(lo));
    return r;
}
__device__ __forceinline__ float bf16r(float x) { return __uint_as_float(pack_bf16(0.f, x) & 0xffff0000u); }
__device__ __forceinline__ uint32_t hmul2(uint32_t a, uint32_t b) {
    uint32_t r;
    asm("mul.rn.bf16x2 %0, %1, %2;" : "=r"(r) : "r"(a), "r"(b));
    return r;
}
__device__ __forceinline__ uint32_t hsub2(uint32_t a, uint32_t b) {
    uint32_t r;
    asm("sub.rn.bf16x2 %0, %1, %2;" : "=r"(r) : "r"(a), "r"(b));
    return r;
}
__device__ __forceinline__ uint32_t hfma2(uint32_t a, uint32_t b, uint32_t c) {
    uint32_t r;
    asm("fma.rn.bf16x2 %0, %1, %2, %3;" : "=r"(r) : "r"(a), "r"(b), "r"(c));
    return r;
}
__device__ __forceinline__ void mma16816(float (&c)[4], const uint32_t (&a)[4], uint32_t b0, uint32_t b1) {
    asm volatile("mma.sync.aligned.m16n8k16.row.col.f32.bf16.bf16.f32 {%0,%1,%2,%3}, {%4,%5,%6,%7}, {%8,%9}, {%0,%1,%2,%3};"
                 : "+f"(c[0]), "+f"(c[1]), "+f"(c[2]), "+f"(c[3])
                 : "r"(a[0]), "r"(a[1]), "r"(a[2]), "r"(a[3]), "r"(b0), "r"(b1));
}
__device__ __forceinline__ void mma16816_z(float (&c)[4], const uint32_t (&a)[4], uint32_t b0, uint32_t b1) {
    asm volatile("mma.sync.aligned.m16n8k16.row.col.f32.bf16.bf16.f32 {%0,%1,%2,%3}, {%4,%5,%6,%7}, {%8,%9}, {%10,%10,%10,%10};"
                 : "=f"(c[0]), "=f"(c[1]), "=f"(c[2]), "=f"(c[3])
                 : "r"(a[0]), "r"(a[1]), "r"(a[2]), "r"(a[3]), "r"(b0), "r"(b1), "f"(0.f));
}
__device__ __forceinline__ void ldsm4(uint32_t (&r)[4], uint32_t addr) {
    asm volatile("ldmatrix.sync.aligned.m8n8.x4.shared.b16 {%0,%1,%2,%3}, [%4];"
                 : "=r"(r[0]), "=r"(r[1]), "=r"(r[2]), "=r"(r[3]) : "r"(addr));
}
__device__ __forceinline__ void ldsm4t(uint32_t (&r)[4], uint32_t addr) {
    asm volatile("ldmatrix.sync.aligned.m8n8.x4.trans.shared.b16 {%0,%1,%2,%3}, [%4];"
                 : "=r"(r[0]), "=r"(r[1]), "=r"(r[2]), "=r"(r[3]) : "r"(addr));
}
__device__ __forceinline__ void mbar_init(uint32_t bar, int cnt) {
    asm volatile("mbarrier.init.shared::cta.b64 [%0], %1;" ::"r"(bar), "r"(cnt) : "memory");
}
__device__ __forceinline__ void mbar_arrive(uint32_t bar) {
    asm volatile("mbarrier.arrive.shared::cta.b64 _, [%0];" ::"r"(bar) : "memory");
}
__device__ __forceinline__ void mbar_expect_tx(uint32_t bar, uint32_t bytes) {
    asm volatile("mbarrier.arrive.expect_tx.shared::cta.b64 _, [%0], %1;" ::"r"(bar), "r"(bytes) : "memory");
}
__device__ __forceinline__ void mbar_wait(uint32_t bar, uint32_t parity) {
    asm volatile(
        "{\n.reg .pred p;\n.reg .u32 n;\nmov.u32 n, 0;\n"
        "WAIT_%=:\n"
        "mbarrier.try_wait.parity.shared::cta.b64 p, [%0], %1, %2;\n"
        "@p bra DONE_%=;\n"
        "add.u32 n, n, 1;\n"
        "setp.lt.u32 p, n, 100000;\n"
        "@p bra WAIT_%=;\n"
        "exit;\n"
        "DONE_%=:\n}\n" ::"r"(bar), "r"(parity), "r"(10000u) : "memory");
}
__device__ __forceinline__ void bulk_g2s(uint32_t dst, const void* src, uint32_t bytes, uint32_t bar) {
    asm volatile("cp.async.bulk.shared::cluster.global.mbarrier::complete_tx::bytes [%0], [%1], %2, [%3];"
                 ::"r"(dst), "l"(src), "r"(bytes), "r"(bar) : "memory");
}
__device__ __forceinline__ void bulk_s2g(void* dst, uint32_t src, uint32_t bytes) {
    asm volatile("cp.async.bulk.global.shared::cta.bulk_group [%0], [%1], %2;" ::"l"(dst), "r"(src), "r"(bytes) : "memory");
}
__device__ __forceinline__ int group_begin(int c, int ngroups) { return (c * ngroups) / NCTA; }

constexpr int P_THREADS = 1024;
constexpr int P1_WARPS = 5;
constexpr int P3_THREADS = P_THREADS - 32 * P1_WARPS;
constexpr int P3_ITERS = 3;
constexpr int W_PITCH = 144;
constexpr int PS_TILE = 0;
constexpr int PS_REC = PS_TILE + P1_WARPS * 8192;
constexpr int PS_PFX = PS_REC + CH * 8;
constexpr int PS_POS = PS_PFX + NCTA * 32;
constexpr int PS_W1 = PS_POS + 60032;
constexpr int PS_W2 = PS_W1 + 64 * W_PITCH;
constexpr int PS_HIST = PS_W2 + 64 * W_PITCH;
constexpr int PS_BAR = PS_HIST + (1280 + 32) * 4;
constexpr int PS_TOTAL = PS_BAR + 64;

__global__ void __launch_bounds__(P_THREADS, 1)
prep_kernel(const __nv_bfloat16* __restrict__ sv, const __nv_bfloat16* __restrict__ pos,
            const int* __restrict__ src, const int* __restrict__ dst,
            const __nv_bfloat16* __restrict__ freqs, const __nv_bfloat16* __restrict__ w1,
            const __nv_bfloat16* __restrict__ w2, int N, int E) {
    extern __shared__ __align__(128) unsigned char smem[];
    const int tid = threadIdx.x, warp = tid >> 5, lane = tid & 31;
    asm volatile("griddepcontrol.launch_dependents;");
    if (tid == 0) STAMP(0);

    if (warp < P1_WARPS) {
        const int g = lane >> 2, t = lane & 3;
        const int tile = warp * gridDim.x + blockIdx.x;
        const int nrows = min(16, N - tile * 16);
        const uint32_t bar = smem_u32(smem + PS_BAR + 8 + 8 * warp);
        unsigned char* tb = smem + PS_TILE + warp * 8192;
        if (nrows > 0 && lane == 0) {
            mbar_init(bar, 1);
            asm volatile("fence.mbarrier_init.release.cluster;" ::: "memory");
            mbar_expect_tx(bar, nrows * 512);
            bulk_g2s(smem_u32(tb), sv + (size_t)tile * 16 * 256, nrows * 512, bar);
        }
        for (int i = tid; i < 64 * 8; i += 32 * P1_WARPS) {
            const int r = i >> 3, c = i & 7;
            *reinterpret_cast<uint4*>(smem + PS_W1 + r * W_PITCH + c * 16) =
                __ldg(reinterpret_cast<const uint4*>(w1 + r * 64) + c);
            const uint4 v = __ldg(reinterpret_cast<const uint4*>(w2 + r * 192 + 64) + c);
            const int tt = c >> 1, j0 = (c & 1) * 4;
            uint32_t* o = reinterpret_cast<uint32_t*>(smem + PS_W2 + r * W_PITCH);
            o[4 * (j0 + 0) + tt] = v.x; o[4 * (j0 + 1) + tt] = v.y;
            o[4 * (j0 + 2) + tt] = v.z; o[4 * (j0 + 3) + tt] = v.w;
        }
        asm volatile("bar.sync 1, %0;" ::"n"(32 * P1_WARPS) : "memory");
        if (tid == 0) STAMP(1);
        if (nrows > 0) {
            mbar_wait(bar, 0);
            if (tid == 0) STAMP(2);
            uint4* r0 = reinterpret_cast<uint4*>(tb + g * 512 + t * 32);
            uint4* r1 = reinterpret_cast<uint4*>(tb + (g + 8) * 512 + t * 32);
            uint32_t h[4][4];
            {
                uint4 xa[2] = {r0[0], r0[1]}, xb[2] = {r1[0], r1[1]};
                const uint32_t* s0 = reinterpret_cast<const uint32_t*>(xa);
                const uint32_t* s1 = reinterpret_cast<const uint32_t*>(xb);
                float a[8][4];
                const int i = lane & 7, hi = (lane >> 3) & 1, nsel = lane >> 4;
#pragma unroll
                for (int q = 0; q < 4; q++) {
                    const int krow = 16 * (i >> 1) + 4 * q + (i & 1) + 2 * hi;
                    const uint32_t af[4] = {s0[2 * q], s1[2 * q], s0[2 * q + 1], s1[2 * q + 1]};
#pragma unroll
                    for (int jp = 0; jp < 4; jp++) {
                        uint32_t b[4];
                        ldsm4t(b, smem_u32(smem + PS_W1 + krow * W_PITCH + (2 * jp + nsel) * 16));
                        if (q == 0) {
                            mma16816_z(a[2 * jp], af, b[0], b[1]);
                            mma16816_z(a[2 * jp + 1], af, b[2], b[3]);
                        } else {
                            mma16816(a[2 * jp], af, b[0], b[1]);
                            mma16816(a[2 * jp + 1], af, b[2], b[3]);
                        }
                    }
                }
#pragma unroll
                for (int j = 0; j < 8; j++) {
                    float f[4];
#pragma unroll
                    for (int e = 0; e < 4; e++) {
                        const float z = bf16r(a[j][e]);
                        f[e] = __fdividef(z, 1.0f + __expf(-z));
                    }
                    h[j >> 1][(j & 1) * 2 + 0] = pack_bf16(f[0], f[1]);
                    h[j >> 1][(j & 1) * 2 + 1] = pack_bf16(f[2], f[3]);
                }
            }
            r0[0] = make_uint4(h[0][0], h[0][2], h[1][0], h[1][2]);
            r0[1] = make_uint4(h[2][0], h[2][2], h[3][0], h[3][2]);
            r1[0] = make_uint4(h[0][1], h[0][3], h[1][1], h[1][3]);
            r1[1] = make_uint4(h[2][1], h[2][3], h[3][1], h[3][3]);
            float p[8][4];
            {
                const int i = lane & 15, nsel = lane >> 4;
#pragma unroll
                for (int q = 0; q < 4; q++) {
#pragma unroll
                    for (int jp = 0; jp < 4; jp++) {
                        uint32_t b[4];
                        ldsm4t(b, smem_u32(smem + PS_W2 + (16 * q + i) * W_PITCH + (2 * jp + nsel) * 16));
                        if (q == 0) {
                            mma16816_z(p[2 * jp], h[0], b[0], b[1]);
                            mma16816_z(p[2 * jp + 1], h[0], b[2], b[3]);
                        } else {
                            mma16816(p[2 * jp], h[q], b[0], b[1]);
                            mma16816(p[2 * jp + 1], h[q], b[2], b[3]);
                        }
                    }
                }
            }
#pragma unroll
            for (int r = 0; r < 2; r++) {
                uint4* row = r ? r1 : r0;
                uint32_t pv[8];
#pragma unroll
                for (int j = 0; j < 8; j++) pv[j] = pack_bf16(p[j][2 * r], p[j][2 * r + 1]);
#pragma unroll
                for (int c = 1; c < 4; c++) {
                    uint4 vx[2] = {row[c * 8], row[c * 8 + 1]};
                    const uint32_t* vv = reinterpret_cast<const uint32_t*>(vx);
                    uint32_t u[8];
#pragma unroll
                    for (int j = 0; j < 8; j++) u[j] = hmul2(pv[j], vv[j]);
                    row[c * 8] = make_uint4(__byte_perm(u[0], u[1], 0x5410), __byte_perm(u[2], u[3], 0x5410),
                                            __byte_perm(u[4], u[5], 0x5410), __byte_perm(u[6], u[7], 0x5410));
                    row[c * 8 + 1] = make_uint4(__byte_perm(u[0], u[1], 0x7632), __byte_perm(u[2], u[3], 0x7632),
                                                __byte_perm(u[4], u[5], 0x7632), __byte_perm(u[6], u[7], 0x7632));
                }
            }
            asm volatile("fence.proxy.async.shared::cta;" ::: "memory");
            __syncwarp();
            if (tid == 0) STAMP(3);
            if (lane == 0) {
                bulk_s2g(g_tab + (size_t)tile * 16 * ROWB, smem_u32(tb), nrows * 512);
                asm volatile("cp.async.bulk.commit_group;" ::: "memory");
                asm volatile("cp.async.bulk.wait_group 0;" ::: "memory");
            }
            if (tid == 0) STAMP(4);
        }
    } else {
        const int ptid = tid - 32 * P1_WARPS, pwarp = warp - P1_WARPS;
        const uint32_t bar = smem_u32(smem + PS_BAR);
        const int posbytes = N * 6;
        if (ptid == 0) {
            mbar_init(bar, 1);
            asm volatile("fence.mbarrier_init.release.cluster;" ::: "memory");
            mbar_expect_tx(bar, posbytes);
            bulk_g2s(smem_u32(smem + PS_POS), pos, posbytes, bar);
        }
        const int npairs = E >> 1;
        const int ppc = (npairs + NCTA - 1) / NCTA;
        const int pbeg = blockIdx.x * ppc, pend = min(pbeg + ppc, npairs);
        int2 es[P3_ITERS], ed[P3_ITERS];
#pragma unroll
        for (int it = 0; it < P3_ITERS; it++) {
            const int p = pbeg + ptid + it * P3_THREADS;
            if (p < pend) {
                es[it] = __ldcs(reinterpret_cast<const int2*>(src) + p);
                ed[it] = __ldcs(reinterpret_cast<const int2*>(dst) + p);
            }
        }
        int* hist = reinterpret_cast<int*>(smem + PS_HIST);
        for (int i = ptid; i < 1280; i += P3_THREADS) hist[i] = 0;
        {
            const int gi = ptid * NCTA + blockIdx.x;
            if (gi < NTAB * NRBF) {
                const int di = gi >> 4, k = gi & 15;
                const float d = __uint_as_float((uint32_t)(DBASE + di) << 16);
                const float arg = bf16r(d * __bfloat162float(freqs[k]));
                const float rbf = bf16r(bf16r(sinf(arg)) / d);
                const float ca = bf16r(bf16r(3.14159265358979f * d) / 5.0f);
                const float fc = 0.5f * bf16r(bf16r(cosf(ca)) + 1.0f);
                g_G[gi] = __float2bfloat16_rn(rbf * fc);
            }
        }
        if (ptid == 0) STAMP(5);
        asm volatile("bar.sync 2, %0;" ::"n"(P3_THREADS) : "memory");
        if (ptid == 0) STAMP(6);
        mbar_wait(bar, 0);
        if (ptid == 0) STAMP(7);
        const uint32_t* pw = reinterpret_cast<const uint32_t*>(smem + PS_POS);
        uint2 rec[P3_ITERS * 2];
        int key[P3_ITERS * 2];
#pragma unroll
        for (int q = 0; q < P3_ITERS * 2; q++) {
            const int it = q >> 1;
            key[q] = -1;
            if (pbeg + ptid + it * P3_THREADS < pend) {
                const int s = (q & 1) ? es[it].y : es[it].x;
                const int dd = (q & 1) ? ed[it].y : ed[it].x;
                const int ws = (s * 3) >> 1, wd = (dd * 3) >> 1;
                const uint32_t sa = pw[ws], sb = pw[ws + 1], da = pw[wd], db = pw[wd + 1];
                const uint32_t shs = (s & 1) << 4, shd = (dd & 1) << 4;
                const uint32_t rxy = hsub2(__funnelshift_r(sa, sb, shs), __funnelshift_r(da, db, shd));
                const uint32_t rz = hsub2(sb >> shs, db >> shd);
                const uint32_t qxy = hmul2(rxy, rxy), qz = hmul2(rz, rz);
                const float sum = (__uint_as_float(qxy << 16) + __uint_as_float(qxy & 0xffff0000u)) + __uint_as_float(qz << 16);
                if (sum < 23.9375f) {
                    const uint32_t exy = hmul2(rxy, 0x3e803e80u), ez = hmul2(rz, 0x3e803e80u);
                    rec[q].x = exy | ((dd & 1) << 14) | ((dd & 2) << 29);
                    rec[q].y = (ez & 0xffffu) | ((dd & 4) << 12) | ((uint32_t)s << 16);
                    const int grp = dd >> 3;
                    key[q] = (grp << 13) | atomicAdd(&hist[grp], 1);
                }
            }
        }
        if (ptid == 0) STAMP(8);
        asm volatile("bar.sync 2, %0;" ::"n"(P3_THREADS) : "memory");
        if (ptid == 0) STAMP(9);
        int2 hv = make_int2(0, 0);
        int incl = 0;
        if (pwarp < 20) {
            hv = reinterpret_cast<int2*>(hist)[ptid];
            incl = hv.x + hv.y;
#pragma unroll
            for (int o = 1; o < 32; o <<= 1) {
                const int v = __shfl_up_sync(0xffffffffu, incl, o);
                if (lane >= o) incl += v;
            }
            if (lane == 31) hist[1280 + pwarp] = incl;
        }
        asm volatile("bar.sync 2, %0;" ::"n"(P3_THREADS) : "memory");
        if (pwarp < 20) {
            int wsum = (lane < pwarp) ? hist[1280 + lane] : 0;
            wsum = __reduce_add_sync(0xffffffffu, wsum);
            const int ex = wsum + incl - hv.x - hv.y;
            reinterpret_cast<int2*>(hist)[ptid] = make_int2(ex, ex + hv.x);
        }
        asm volatile("bar.sync 2, %0;" ::"n"(P3_THREADS) : "memory");
        if (ptid == 0) STAMP(10);
        uint2* srec = reinterpret_cast<uint2*>(smem + PS_REC);
#pragma unroll
        for (int q = 0; q < P3_ITERS * 2; q++)
            if (key[q] >= 0) srec[hist[key[q] >> 13] + (key[q] & 8191)] = rec[q];
        const int ngroups = (N + GRP - 1) / GRP;
        unsigned short* spfx = reinterpret_cast<unsigned short*>(smem + PS_PFX);
        for (int i = ptid; i < NCTA * 16; i += P3_THREADS)
            spfx[i] = (unsigned short)hist[min(group_begin(i >> 4, ngroups) + (i & 15), ngroups)];
        asm volatile("fence.proxy.async.shared::cta;" ::: "memory");
        asm volatile("bar.sync 2, %0;" ::"n"(P3_THREADS) : "memory");
        if (ptid == 0) {
            STAMP(11);
            const int total = hist[ngroups];
            const int bytes = ((total + 1) >> 1) * 16;
            if (bytes > 0) bulk_s2g(g_rec + blockIdx.x * CH, smem_u32(srec), bytes);
            bulk_s2g(g_pfx + blockIdx.x * NCTA * 16, smem_u32(spfx), NCTA * 32);
            asm volatile("cp.async.bulk.commit_group;" ::: "memory");
            asm volatile("cp.async.bulk.wait_group 0;" ::: "memory");
            STAMP(12);
        }
    }
}

constexpr int UNITS = 3;
constexpr int STAGES = 3;
constexpr int M_THREADS = UNITS * 128 + 128;
constexpr int ST_G = 32 * ROWB;
constexpr int ST_S = ST_G + 1024;
constexpr int ST_R = ST_S + 512;
constexpr int ST_META = ST_R + 192;
constexpr int STAGE_BYTES = ST_R + 256;
constexpr int RCAP = 4608;
constexpr int MAXQ = 10;
constexpr int HOT0 = 0x3F00 - DBASE;
constexpr int MS_RAW = UNITS * STAGES * STAGE_BYTES;
constexpr int MS_IDX = MS_RAW + RCAP * 8;
constexpr int MS_GH = MS_IDX + RCAP * 2;
constexpr int MS_PF = MS_GH + (NTAB - HOT0) * 32;
constexpr int MS_DELTA = MS_PF + NCTA * 32;
constexpr int MS_MISC = MS_DELTA + 136 * 4;
constexpr int MS_BAR = MS_MISC + 32 * 4;
constexpr int M_SMEM = MS_BAR + (2 * UNITS * STAGES + 1) * 8;
static_assert(M_SMEM <= 232448, "smem");
static_assert(MS_BAR % 8 == 0 && MS_GH % 16 == 0 && MS_PF % 16 == 0, "align");
static_assert(MAXQ * 136 * 4 <= RCAP * 2, "overflow table");

__global__ void __launch_bounds__(M_THREADS, 1)
main_kernel(const __nv_bfloat16* __restrict__ sv, const __nv_bfloat16* __restrict__ w2,
            const __nv_bfloat16* __restrict__ wrbf, __nv_bfloat16* __restrict__ out, int N) {
    extern __shared__ __align__(128) unsigned char smem[];
    const int tid = threadIdx.x, warp = tid >> 5, lane = tid & 31;
    const int g = lane >> 2, t = lane & 3;
    const int ngroups = (N + GRP - 1) / GRP;
    const int q0 = group_begin(blockIdx.x, ngroups);
    const int nq = group_begin(blockIdx.x + 1, ngroups) - q0;
    const uint32_t sbase = smem_u32(smem);
    const uint32_t rawbar = sbase + MS_BAR + 2 * UNITS * STAGES * 8;
    int* misc = reinterpret_cast<int*>(smem + MS_MISC);
    const bool is_prod = warp >= UNITS * 4;
    const int unit = is_prod ? warp - UNITS * 4 : warp >> 2;
    const int w = warp & 3;

    if (tid == 0) {
        STAMP(16);
        for (int i = 0; i < UNITS * STAGES; i++) {
            mbar_init(sbase + MS_BAR + i * 16, 33);
            mbar_init(sbase + MS_BAR + i * 16 + 8, 4);
        }
        mbar_init(rawbar, 1);
        asm volatile("fence.mbarrier_init.release.cluster;" ::: "memory");
        misc[24] = UNITS;
    }
    uint32_t wa[3][4], pa[2][4][4];
    if (!is_prod) {
        const int c = 16 * w + 2 * g;
#pragma unroll
        for (int p = 0; p < 3; p++)
#pragma unroll
            for (int kh = 0; kh < 2; kh++) {
                const uint32_t lo = __ldg(reinterpret_cast<const uint32_t*>(wrbf + (2 * t + 8 * kh) * 192 + p * 64 + c));
                const uint32_t hi = __ldg(reinterpret_cast<const uint32_t*>(wrbf + (2 * t + 8 * kh + 1) * 192 + p * 64 + c));
                wa[p][2 * kh + 0] = __byte_perm(lo, hi, 0x5410);
                wa[p][2 * kh + 1] = __byte_perm(lo, hi, 0x7632);
            }
#pragma unroll
        for (int p = 0; p < 2; p++)
#pragma unroll
            for (int q = 0; q < 4; q++)
#pragma unroll
                for (int kh = 0; kh < 2; kh++) {
                    const int r = 8 * (t + 4 * kh) + 2 * q;
                    const uint32_t lo = __ldg(reinterpret_cast<const uint32_t*>(w2 + r * 192 + p * 128 + c));
                    const uint32_t hi = __ldg(reinterpret_cast<const uint32_t*>(w2 + (r + 1) * 192 + p * 128 + c));
                    pa[p][q][2 * kh + 0] = __byte_perm(lo, hi, 0x5410);
                    pa[p][q][2 * kh + 1] = __byte_perm(lo, hi, 0x7632);
                }
    }
    if (tid == 0) STAMP(17);
    asm volatile("griddepcontrol.wait;" ::: "memory");
    if (tid == 0) STAMP(18);

    unsigned short* pf = reinterpret_cast<unsigned short*>(smem + MS_PF);
    int* delta = reinterpret_cast<int*>(smem + MS_DELTA);
    int a0 = 0, len = 0, incl = 0;
    if (warp < 5) {
        if (tid < NCTA) {
            const uint4* bp = reinterpret_cast<const uint4*>(g_pfx + (tid * NCTA + blockIdx.x) * 16);
            const uint4 b0 = __ldcg(bp), b1 = __ldcg(bp + 1);
            if (tid == 0) bulk_g2s(sbase + MS_GH, g_G + HOT0 * NRBF, (NTAB - HOT0) * 32, rawbar);
            reinterpret_cast<uint4*>(pf)[tid * 2] = b0;
            reinterpret_cast<uint4*>(pf)[tid * 2 + 1] = b1;
            a0 = (b0.x & 0xffffu) & ~1;
            const int wi = nq >> 1;
            uint32_t ew = (wi & 4) ? ((wi & 2) ? ((wi & 1) ? b1.w : b1.z) : ((wi & 1) ? b1.y : b1.x))
                                   : ((wi & 2) ? ((wi & 1) ? b0.w : b0.z) : ((wi & 1) ? b0.y : b0.x));
            const int e = (nq & 1) ? (int)(ew >> 16) : (int)(ew & 0xffffu);
            len = ((e + 1) & ~1) - a0;
        }
        incl = len;
#pragma unroll
        for (int o = 1; o < 32; o <<= 1) {
            const int v = __shfl_up_sync(0xffffffffu, incl, o);
            if (lane >= o) incl += v;
        }
        if (lane == 31) misc[warp] = incl;
    }
    __syncthreads();
    if (tid == 0) STAMP(19);
    const int rtotal = misc[0] + misc[1] + misc[2] + misc[3] + misc[4];
    const bool fits = rtotal <= RCAP;
    if (tid < NCTA) {
        int off = incl - len;
        for (int i = 0; i < warp; i++) off += misc[i];
        delta[tid] = off - a0;
        if (tid == 0) mbar_expect_tx(rawbar, (fits ? rtotal * 8 : 0) + (NTAB - HOT0) * 32);
        if (fits && len > 0) bulk_g2s(sbase + MS_RAW + off * 8, g_rec + tid * CH + a0, len * 8, rawbar);
    }
    int cq[5], pre = 0;
    const int qw = warp - 5;
    if (qw >= 0 && qw < nq) {
        int sum = 0;
#pragma unroll
        for (int k = 0; k < 5; k++) {
            const int p = lane * 5 + k;
            cq[k] = p < NCTA ? (int)pf[p * 16 + qw + 1] - (int)pf[p * 16 + qw] : 0;
            sum += cq[k];
        }
        int in2 = sum;
#pragma unroll
        for (int o = 1; o < 32; o <<= 1) {
            const int v = __shfl_up_sync(0xffffffffu, in2, o);
            if (lane >= o) in2 += v;
        }
        pre = in2 - sum;
        if (lane == 31) misc[8 + qw] = in2;
    }
    __syncthreads();
    if (qw >= 0 && qw < nq) {
        if (fits) {
            int base = (lane < qw) ? misc[8 + lane] : 0;
            base = __reduce_add_sync(0xffffffffu, base) + pre;
            unsigned short* idx = reinterpret_cast<unsigned short*>(smem + MS_IDX);
#pragma unroll
            for (int k = 0; k < 5; k++) {
                const int p = lane * 5 + k;
                if (cq[k] > 0) {
                    const int r = delta[p] + pf[p * 16 + qw];
                    for (int c = 0; c < cq[k]; c++) idx[base + c] = (unsigned short)(r + c);
                    base += cq[k];
                }
            }
        } else {
            int* prq = reinterpret_cast<int*>(smem + MS_IDX) + qw * 136;
#pragma unroll
            for (int k = 0; k < 5; k++) {
                const int p = lane * 5 + k;
                if (p < NCTA) prq[p] = pre;
                pre += cq[k];
            }
        }
    }
    __syncthreads();
    if (tid == 0) STAMP(20);

    const uint32_t ubase = sbase + unit * STAGES * STAGE_BYTES;
    const uint32_t ubar = sbase + MS_BAR + unit * STAGES * 16;
    if (is_prod) {
        asm volatile("setmaxnreg.dec.sync.aligned.u32 56;");
        if (unit < UNITS) {
            mbar_wait(rawbar, 0);
            if (unit == 0 && lane == 0) STAMP(21);
            const uint2* raw = reinterpret_cast<const uint2*>(smem + MS_RAW);
            const unsigned short* idx = reinterpret_cast<const unsigned short*>(smem + MS_IDX);
            const unsigned char* gsrc = g_tab + (lane & 7) * 16;
            const uint32_t d0 = (lane >> 3) * ROWB + (((lane & 7) ^ (lane >> 3)) << 4);
            const uint32_t d1 = ((lane >> 3) + 4) * ROWB + (((lane & 7) ^ ((lane >> 3) + 4)) << 4);
            const uint32_t roff = ST_R + ((lane >> 1) & 3) * 16 + (lane >> 3) * 4 + (lane & 1) * 2;
            const uint32_t gx = ((lane >> 2) & 1) << 4;
            int st = 0, ph = 1;
            int q = unit;
            while (q < nq) {
                int base = (lane < q) ? misc[8 + lane] : 0;
                base = __reduce_add_sync(0xffffffffu, base) + lane;
                const int cnt = misc[8 + q];
                int rem = cnt;
                uint32_t flags = 1u | ((uint32_t)(q0 + q) << 4);
                do {
                    const bool valid = lane < rem;
                    uint2 r = make_uint2(0, 0);
                    if (fits) {
                        if (valid) r = raw[idx[base]];
                    } else if (valid) {
                        const int j = cnt - rem + lane;
                        const int* prq = reinterpret_cast<const int*>(smem + MS_IDX) + q * 136;
                        int lo = 0, hi = NCTA;
                        while (hi - lo > 1) {
                            const int mid = (lo + hi) >> 1;
                            if (prq[mid] <= j) lo = mid; else hi = mid;
                        }
                        r = __ldcg(g_rec + lo * CH + pf[lo * 16 + q] + (j - prq[lo]));
                    }
                    base += 32;
                    const uint32_t rxy = hmul2(r.x & 0xbfffbfffu, 0x40804080u);
                    const uint32_t rz2 = hmul2(r.y & 0x0000bfffu, 0x40804080u);
                    const uint32_t qxy = hmul2(rxy, rxy), qz = hmul2(rz2, rz2);
                    const float sum = bf16r((__uint_as_float(qxy << 16) + __uint_as_float(qxy & 0xffff0000u)) + __uint_as_float(qz << 16));
                    float sq;
                    asm("sqrt.approx.ftz.f32 %0, %1;" : "=f"(sq) : "f"(bf16r(sum + 1e-8f)));
                    const uint32_t dbits = pack_bf16(0.f, sq);
                    float rinv;
                    asm("rcp.approx.ftz.f32 %0, %1;" : "=f"(rinv) : "f"(__uint_as_float(dbits)));
                    const int di = min(max((int)(dbits >> 16) - DBASE, 0), NTAB - 1);
                    const uint4* gp = (di >= HOT0) ? reinterpret_cast<const uint4*>(smem + MS_GH - HOT0 * 32) + 2 * di
                                                   : reinterpret_cast<const uint4*>(g_G) + 2 * di;
                    uint4 g0 = make_uint4(0, 0, 0, 0), g1 = g0;
                    if (valid) { g0 = gp[0]; g1 = gp[1]; }
                    const uint32_t r01 = pack_bf16(__uint_as_float(rxy << 16) * rinv, __uint_as_float(rxy & 0xffff0000u) * rinv);
                    const uint32_t r2 = pack_bf16(__uint_as_float(rz2 << 16) * rinv, 0.f);
                    const uint32_t one = valid ? ((r.x & 0x4000u) ? 0x3f800000u : 0x00003f80u) : 0u;
                    const bool b1 = (r.x & 0x40000000u) != 0, b2 = (r.y & 0x4000u) != 0;
                    const uint32_t srcv = r.y >> 16;

                    mbar_wait(ubar + st * 16 + 8, ph);
                    const uint32_t sb = ubase + st * STAGE_BYTES;
#pragma unroll
                    for (int k = 0; k < 8; k++) {
                        const int e = k * 4 + (lane >> 3);
                        const uint32_t s = __shfl_sync(0xffffffffu, srcv, e);
                        const unsigned char* gq = gsrc + (size_t)s * ROWB;
                        const uint32_t dp = sb + ((k & 1) ? d1 : d0) + (k >> 1) * 8 * ROWB;
                        asm volatile("{\n.reg .pred p;\nsetp.ge.s32 p, %2, %3;\n"
                                     "cp.async.cg.shared.global [%0], [%1], 16, p;\n"
                                     "cp.async.cg.shared.global [%0+128], [%1+128], 16, p;\n"
                                     "cp.async.cg.shared.global [%0+256], [%1+256], 16, p;\n"
                                     "cp.async.cg.shared.global [%0+384], [%1+384], 16, p;\n}\n"
                                     ::"r"(dp), "l"(gq), "r"(e), "r"(rem) : "memory");
                    }
                    asm volatile("cp.async.mbarrier.arrive.noinc.shared::cta.b64 [%0];" ::"r"(ubar + st * 16) : "memory");
                    asm volatile("st.shared.v4.u32 [%0], {%1,%2,%3,%4};" ::"r"(sb + ST_S + lane * 16),
                                 "r"((!b1 && !b2) ? one : 0u), "r"((b1 && !b2) ? one : 0u),
                                 "r"((!b1 && b2) ? one : 0u), "r"((b1 && b2) ? one : 0u) : "memory");
                    asm volatile("st.shared.u16 [%0], %1;" ::"r"(sb + roff), "h"((unsigned short)(r01 & 0xffffu)) : "memory");
                    asm volatile("st.shared.u16 [%0], %1;" ::"r"(sb + roff + 64), "h"((unsigned short)(r01 >> 16)) : "memory");
                    asm volatile("st.shared.u16 [%0], %1;" ::"r"(sb + roff + 128), "h"((unsigned short)(r2 & 0xffffu)) : "memory");
                    asm volatile("st.shared.v4.u32 [%0], {%1,%2,%3,%4};" ::"r"(sb + ST_G + lane * 32 + gx),
                                 "r"(g0.x), "r"(g0.y), "r"(g0.z), "r"(g0.w) : "memory");
                    asm volatile("st.shared.v4.u32 [%0], {%1,%2,%3,%4};" ::"r"(sb + ST_G + lane * 32 + (gx ^ 16u)),
                                 "r"(g1.x), "r"(g1.y), "r"(g1.z), "r"(g1.w) : "memory");
                    asm volatile("st.shared.u32 [%0], %1;" ::"r"(sb + ST_META),
                                 "r"(flags | (rem <= 32 ? 2u : 0u) | (rem > 16 ? 4u : 0u)) : "memory");
                    __syncwarp();
                    if (lane == 0) mbar_arrive(ubar + st * 16);
                    if (++st == STAGES) { st = 0; ph ^= 1; }
                    flags &= ~1u;
                    rem -= 32;
                } while (rem > 0);
                int nx = 0;
                if (lane == 0) nx = atomicAdd(&misc[24], 1);
                q = __shfl_sync(0xffffffffu, nx, 0);
            }
            mbar_wait(ubar + st * 16 + 8, ph);
            asm volatile("st.shared.u32 [%0], %1;" ::"r"(ubase + st * STAGE_BYTES + ST_META), "r"(8u) : "memory");
            __syncwarp();
            mbar_arrive(ubar + st * 16);
            if (lane == 0) mbar_arrive(ubar + st * 16);
            if (lane == 0) STAMP(22 + unit);
        }
    } else {
        asm volatile("setmaxnreg.inc.sync.aligned.u32 152;");
        float acc[4][4];
#pragma unroll
        for (int c = 0; c < 4; c++)
#pragma unroll
            for (int e = 0; e < 4; e++) acc[c][e] = 0.f;
        uint32_t svv[4][2];
        const int erow = (lane & 7) + 8 * (lane >> 4);
        const int ehalf = (lane >> 3) & 1;
        const uint32_t hoff = erow * ROWB + ((uint32_t)(ehalf ^ (lane & 7)) << 4);
        const uint32_t uoff = (hoff ^ (uint32_t)(w << 5)) + 128;
        const uint32_t goff = ST_G + erow * 32 + ((ehalf ^ ((erow >> 2) & 1)) << 4);
        const uint32_t soff = ST_S + lane * 16, roff = ST_R + t * 16;
        const int ooff = 2 * t * 128 + 8 * w + g;
        int st = 0, ph = 0;
        bool first = true;
        while (true) {
            mbar_wait(ubar + st * 16, ph);
            if (first && tid == 0) STAMP(25);
            first = false;
            const uint32_t sb = ubase + st * STAGE_BYTES;
            uint32_t flags;
            asm volatile("ld.shared.u32 %0, [%1];" : "=r"(flags) : "r"(sb + ST_META));
            uint32_t sf[4], rr[3][4];
            ldsm4t(sf, sb + soff);
#pragma unroll
            for (int j = 0; j < 3; j++)
                asm volatile("ld.shared.v4.u32 {%0,%1,%2,%3}, [%4];" : "=r"(rr[j][0]), "=r"(rr[j][1]), "=r"(rr[j][2]), "=r"(rr[j][3])
                             : "r"(sb + roff + j * 64));
            if (flags & 8u) break;
            const int node0 = (int)(flags >> 4) * GRP + 2 * t;
            if (flags & 1u) {
                const uint32_t* ip = reinterpret_cast<const uint32_t*>(sv) + (size_t)(flags >> 4) * (GRP * 128) + ooff;
#pragma unroll
                for (int b = 0; b < 2; b++)
#pragma unroll
                    for (int c = 0; c < 4; c++) svv[c][b] = (node0 + b < N) ? __ldg(ip + b * 128 + c * 32) : 0u;
            }
#pragma unroll
            for (int s = 0; s < 2; s++) {
                if (s == 0 || (flags & 4u)) {
                    const uint32_t ha = sb + hoff + s * 16 * ROWB;
                    const uint32_t ua = sb + uoff + s * 16 * ROWB;
                    float ps[2][4], pv[2][4];
#pragma unroll
                    for (int q = 0; q < 4; q++) {
                        uint32_t hb[4];
                        ldsm4(hb, ha ^ (uint32_t)(q << 5));
                        if (q == 0) {
                            mma16816_z(ps[0], pa[0][0], hb[0], hb[1]); mma16816_z(ps[1], pa[0][0], hb[2], hb[3]);
                            mma16816_z(pv[0], pa[1][0], hb[0], hb[1]); mma16816_z(pv[1], pa[1][0], hb[2], hb[3]);
                        } else {
                            mma16816(ps[0], pa[0][q], hb[0], hb[1]); mma16816(ps[1], pa[0][q], hb[2], hb[3]);
                            mma16816(pv[0], pa[1][q], hb[0], hb[1]); mma16816(pv[1], pa[1][q], hb[2], hb[3]);
                        }
                    }
                    uint32_t gb[4];
                    ldsm4(gb, sb + goff + s * 512);
                    float f0[4], f1[4];
                    uint32_t m[4], mvr[4], wv[4];
                    mma16816_z(f0, wa[1], gb[0], gb[1]); mma16816_z(f1, wa[1], gb[2], gb[3]);
                    wv[0] = pack_bf16(f0[0], f0[1]); wv[1] = pack_bf16(f0[2], f0[3]);
                    wv[2] = pack_bf16(f1[0], f1[1]); wv[3] = pack_bf16(f1[2], f1[3]);
                    mma16816_z(f0, wa[0], gb[0], gb[1]); mma16816_z(f1, wa[0], gb[2], gb[3]);
                    m[0] = pack_bf16(f0[0] * ps[0][0], f0[1] * ps[0][1]); m[1] = pack_bf16(f0[2] * ps[0][2], f0[3] * ps[0][3]);
                    m[2] = pack_bf16(f1[0] * ps[1][0], f1[1] * ps[1][1]); m[3] = pack_bf16(f1[2] * ps[1][2], f1[3] * ps[1][3]);
                    mma16816(acc[0], m, sf[2 * s], sf[2 * s + 1]);
                    mma16816_z(f0, wa[2], gb[0], gb[1]); mma16816_z(f1, wa[2], gb[2], gb[3]);
                    mvr[0] = pack_bf16(f0[0] * pv[0][0], f0[1] * pv[0][1]); mvr[1] = pack_bf16(f0[2] * pv[0][2], f0[3] * pv[0][3]);
                    mvr[2] = pack_bf16(f1[0] * pv[1][0], f1[1] * pv[1][1]); mvr[3] = pack_bf16(f1[2] * pv[1][2], f1[3] * pv[1][3]);
#pragma unroll
                    for (int j = 0; j < 3; j++) {
                        uint32_t x[4];
                        ldsm4t(x, ua + j * 128);
#pragma unroll
                        for (int e = 0; e < 4; e++) m[e] = hfma2(mvr[e], rr[j][2 * s + (e >> 1)], hmul2(x[e], wv[e]));
                        mma16816(acc[j + 1], m, sf[2 * s], sf[2 * s + 1]);
                    }
                }
            }
            __syncwarp();
            if (lane == 0) mbar_arrive(ubar + st * 16 + 8);
            if (++st == STAGES) { st = 0; ph ^= 1; }
            if (flags & 2u) {
                uint32_t* op = reinterpret_cast<uint32_t*>(out) + (size_t)(flags >> 4) * (GRP * 128) + ooff;
#pragma unroll
                for (int b = 0; b < 2; b++) {
#pragma unroll
                    for (int c = 0; c < 4; c++) {
                        const uint32_t v = svv[c][b];
                        const uint32_t o = pack_bf16(__uint_as_float(v << 16) + acc[c][b],
                                                     __uint_as_float(v & 0xffff0000u) + acc[c][2 + b]);
                        if (node0 + b < N) op[b * 128 + c * 32] = o;
                    }
                }
#pragma unroll
                for (int c = 0; c < 4; c++)
#pragma unroll
                    for (int e = 0; e < 4; e++) acc[c][e] = 0.f;
            }
        }
        if (lane == 0 && w == 0) STAMP(26 + unit);
    }
}

}

extern "C" void kernel_launch(void* const* d_in, const int* in_sizes, int n_in, void* d_out, int out_size) {
    const __nv_bfloat16* sv = (const __nv_bfloat16*)d_in[0];
    const __nv_bfloat16* pos = (const __nv_bfloat16*)d_in[1];
    const int* src = (const int*)d_in[2];
    const int* dst = (const int*)d_in[3];
    const __nv_bfloat16* freqs = (const __nv_bfloat16*)d_in[4];
    const __nv_bfloat16* w1 = (const __nv_bfloat16*)d_in[5];
    const __nv_bfloat16* w2 = (const __nv_bfloat16*)d_in[6];
    const __nv_bfloat16* wrbf = (const __nv_bfloat16*)d_in[7];
    __nv_bfloat16* out = (__nv_bfloat16*)d_out;
    const int N = in_sizes[1] / 3;
    const int E = in_sizes[2];

    static bool init = false;
    if (!init) {
        cudaFuncSetAttribute(prep_kernel, cudaFuncAttributeMaxDynamicSharedMemorySize, PS_TOTAL);
        cudaFuncSetAttribute(main_kernel, cudaFuncAttributeMaxDynamicSharedMemorySize, M_SMEM);
        init = true;
    }
    cudaStream_t stream = cudaStreamPerThread;
    prep_kernel<<<NCTA, P_THREADS, PS_TOTAL, stream>>>(sv, pos, src, dst, freqs, w1, w2, N, E);

    cudaLaunchConfig_t cfg = {};
    cfg.gridDim = dim3(NCTA);
    cfg.blockDim = dim3(M_THREADS);
    cfg.dynamicSmemBytes = M_SMEM;
    cfg.stream = stream;
    cudaLaunchAttribute at[1];
    at[0].id = cudaLaunchAttributeProgrammaticStreamSerialization;
    at[0].val.programmaticStreamSerializationAllowed = 1;
    cfg.attrs = at;
    cfg.numAttrs = 1;
    cudaLaunchKernelEx(&cfg, main_kernel, sv, w2, wrbf, out, N);
}
```

```cpp
#include <cuda_runtime.h>
#include <cuda_bf16.h>
#include <stdint.h>

namespace {

constexpr int D = 64;
constexpr int NRBF = 16;
constexpr int MAXN = 10000;
constexpr int MAXE = 640000;
constexpr int NCTA = 132;
constexpr int GRP = 8;
constexpr int MAXG = (MAXN + GRP - 1) / GRP;
constexpr int CH = 4864;
constexpr int DBASE = 0x38C0;
constexpr int DEND = 0x40A0;
constexpr int NTAB = DEND - DBASE;
constexpr int ROWB = 512;

__device__ __align__(128) unsigned char g_tab[(size_t)(MAXN + 16) * ROWB];
__device__ __align__(128) __nv_bfloat16 g_G[NTAB * NRBF];
__device__ __align__(128) uint2 g_rec[NCTA * CH];
__device__ __align__(128) unsigned short g_pfx[NCTA * NCTA * 16];

#define STAMP(k) do {} while (0)

__device__ __forceinline__ uint32_t smem_u32(const void* p) { return (uint32_t)__cvta_generic_to_shared(p); }
__device__ __forceinline__ uint32_t pack_bf16(float lo, float hi) {
    uint32_t r;
    asm("cvt.rn.bf16x2.f32 %0, %1, %2;" : "=r"(r) : "f"(hi), "f"(lo));
    return r;
}
__device__ __forceinline__ float bf16r(float x) { return __uint_as_float(pack_bf16(0.f, x) & 0xffff0000u); }
__device__ __forceinline__ uint32_t hmul2(uint32_t a, uint32_t b) {
    uint32_t r;
    asm("mul.rn.bf16x2 %0, %1, %2;" : "=r"(r) : "r"(a), "r"(b));
    return r;
}
__device__ __forceinline__ uint32_t hsub2(uint32_t a, uint32_t b) {
    uint32_t r;
    asm("sub.rn.bf16x2 %0, %1, %2;" : "=r"(r) : "r"(a), "r"(b));
    return r;
}
__device__ __forceinline__ uint32_t hfma2(uint32_t a, uint32_t b, uint32_t c) {
    uint32_t r;
    asm("fma.rn.bf16x2 %0, %1, %2, %3;" : "=r"(r) : "r"(a), "r"(b), "r"(c));
    return r;
}
__device__ __forceinline__ void mma16816(float (&c)[4], const uint32_t (&a)[4], uint32_t b0, uint32_t b1) {
    asm volatile("mma.sync.aligned.m16n8k16.row.col.f32.bf16.bf16.f32 {%0,%1,%2,%3}, {%4,%5,%6,%7}, {%8,%9}, {%0,%1,%2,%3};"
                 : "+f"(c[0]), "+f"(c[1]), "+f"(c[2]), "+f"(c[3])
                 : "r"(a[0]), "r"(a[1]), "r"(a[2]), "r"(a[3]), "r"(b0), "r"(b1));
}
__device__ __forceinline__ void mma16816_z(float (&c)[4], const uint32_t (&a)[4], uint32_t b0, uint32_t b1) {
    asm volatile("mma.sync.aligned.m16n8k16.row.col.f32.bf16.bf16.f32 {%0,%1,%2,%3}, {%4,%5,%6,%7}, {%8,%9}, {%10,%10,%10,%10};"
                 : "=f"(c[0]), "=f"(c[1]), "=f"(c[2]), "=f"(c[3])
                 : "r"(a[0]), "r"(a[1]), "r"(a[2]), "r"(a[3]), "r"(b0), "r"(b1), "f"(0.f));
}
__device__ __forceinline__ void ldsm4(uint32_t (&r)[4], uint32_t addr) {
    asm volatile("ldmatrix.sync.aligned.m8n8.x4.shared.b16 {%0,%1,%2,%3}, [%4];"
                 : "=r"(r[0]), "=r"(r[1]), "=r"(r[2]), "=r"(r[3]) : "r"(addr));
}
__device__ __forceinline__ void ldsm4t(uint32_t (&r)[4], uint32_t addr) {
    asm volatile("ldmatrix.sync.aligned.m8n8.x4.trans.shared.b16 {%0,%1,%2,%3}, [%4];"
                 : "=r"(r[0]), "=r"(r[1]), "=r"(r[2]), "=r"(r[3]) : "r"(addr));
}
__device__ __forceinline__ void mbar_init(uint32_t bar, int cnt) {
    asm volatile("mbarrier.init.shared::cta.b64 [%0], %1;" ::"r"(bar), "r"(cnt) : "memory");
}
__device__ __forceinline__ void mbar_arrive(uint32_t bar) {
    asm volatile("mbarrier.arrive.shared::cta.b64 _, [%0];" ::"r"(bar) : "memory");
}
__device__ __forceinline__ void mbar_expect_tx(uint32_t bar, uint32_t bytes) {
    asm volatile("mbarrier.arrive.expect_tx.shared::cta.b64 _, [%0], %1;" ::"r"(bar), "r"(bytes) : "memory");
}
__device__ __forceinline__ void mbar_wait(uint32_t bar, uint32_t parity) {
    asm volatile(
        "{\n.reg .pred p;\n.reg .u32 n;\nmov.u32 n, 0;\n"
        "WAIT_%=:\n"
        "mbarrier.try_wait.parity.shared::cta.b64 p, [%0], %1, %2;\n"
        "@p bra DONE_%=;\n"
        "add.u32 n, n, 1;\n"
        "setp.lt.u32 p, n, 100000;\n"
        "@p bra WAIT_%=;\n"
        "exit;\n"
        "DONE_%=:\n}\n" ::"r"(bar), "r"(parity), "r"(10000u) : "memory");
}
__device__ __forceinline__ void bulk_g2s(uint32_t dst, const void* src, uint32_t bytes, uint32_t bar) {
    asm volatile("cp.async.bulk.shared::cluster.global.mbarrier::complete_tx::bytes [%0], [%1], %2, [%3];"
                 ::"r"(dst), "l"(src), "r"(bytes), "r"(bar) : "memory");
}
__device__ __forceinline__ void bulk_s2g(void* dst, uint32_t src, uint32_t bytes) {
    asm volatile("cp.async.bulk.global.shared::cta.bulk_group [%0], [%1], %2;" ::"l"(dst), "r"(src), "r"(bytes) : "memory");
}
__device__ __forceinline__ int group_begin(int c, int ngroups) { return (c * ngroups) / NCTA; }

constexpr int P_THREADS = 1024;
constexpr int P1_WARPS = 5;
constexpr int P3_THREADS = P_THREADS - 32 * P1_WARPS;
constexpr int P3_ITERS = 3;
constexpr int W_PITCH = 144;
constexpr int PS_TILE = 0;
constexpr int PS_REC = PS_TILE + P1_WARPS * 8192;
constexpr int PS_PFX = PS_REC + CH * 8;
constexpr int PS_POS = PS_PFX + NCTA * 32;
constexpr int PS_W1 = PS_POS + 60032;
constexpr int PS_W2 = PS_W1 + 64 * W_PITCH;
constexpr int PS_HIST = PS_W2 + 64 * W_PITCH;
constexpr int PS_BAR = PS_HIST + (1280 + 32) * 4;
constexpr int PS_TOTAL = PS_BAR + 64;

__global__ void __launch_bounds__(P_THREADS, 1)
prep_kernel(const __nv_bfloat16* __restrict__ sv, const __nv_bfloat16* __restrict__ pos,
            const int* __restrict__ src, const int* __restrict__ dst,
            const __nv_bfloat16* __restrict__ freqs, const __nv_bfloat16* __restrict__ w1,
            const __nv_bfloat16* __restrict__ w2, int N, int E) {
    extern __shared__ __align__(1024) unsigned char smem[];
    const int tid = threadIdx.x, warp = tid >> 5, lane = tid & 31;
    asm volatile("griddepcontrol.launch_dependents;");
    if (tid == 0) STAMP(0);

    if (warp < P1_WARPS) {
        const int g = lane >> 2, t = lane & 3;
        const int tile = warp * gridDim.x + blockIdx.x;
        const int nrows = min(16, N - tile * 16);
        const uint32_t bar = smem_u32(smem + PS_BAR + 8 + 8 * warp);
        unsigned char* tb = smem + PS_TILE + warp * 8192;
        if (nrows > 0 && lane == 0) {
            mbar_init(bar, 1);
            asm volatile("fence.mbarrier_init.release.cluster;" ::: "memory");
            mbar_expect_tx(bar, nrows * 512);
            bulk_g2s(smem_u32(tb), sv + (size_t)tile * 16 * 256, nrows * 512, bar);
        }
        for (int i = tid; i < 64 * 8; i += 32 * P1_WARPS) {
            const int r = i >> 3, c = i & 7;
            *reinterpret_cast<uint4*>(smem + PS_W1 + r * W_PITCH + c * 16) =
                __ldg(reinterpret_cast<const uint4*>(w1 + r * 64) + c);
            const uint4 v = __ldg(reinterpret_cast<const uint4*>(w2 + r * 192 + 64) + c);
            const int tt = c >> 1, j0 = (c & 1) * 4;
            uint32_t* o = reinterpret_cast<uint32_t*>(smem + PS_W2 + r * W_PITCH);
            o[4 * (j0 + 0) + tt] = v.x; o[4 * (j0 + 1) + tt] = v.y;
            o[4 * (j0 + 2) + tt] = v.z; o[4 * (j0 + 3) + tt] = v.w;
        }
        asm volatile("bar.sync 1, %0;" ::"n"(32 * P1_WARPS) : "memory");
        if (tid == 0) STAMP(1);
        if (nrows > 0) {
            mbar_wait(bar, 0);
            if (tid == 0) STAMP(2);
            uint4* r0 = reinterpret_cast<uint4*>(tb + g * 512 + t * 32);
            uint4* r1 = reinterpret_cast<uint4*>(tb + (g + 8) * 512 + t * 32);
            uint32_t h[4][4];
            {
                uint4 xa[2] = {r0[0], r0[1]}, xb[2] = {r1[0], r1[1]};
                const uint32_t* s0 = reinterpret_cast<const uint32_t*>(xa);
                const uint32_t* s1 = reinterpret_cast<const uint32_t*>(xb);
                float a[8][4];
                const int i = lane & 7, hi = (lane >> 3) & 1, nsel = lane >> 4;
#pragma unroll
                for (int q = 0; q < 4; q++) {
                    const int krow = 16 * (i >> 1) + 4 * q + (i & 1) + 2 * hi;
                    const uint32_t af[4] = {s0[2 * q], s1[2 * q], s0[2 * q + 1], s1[2 * q + 1]};
#pragma unroll
                    for (int jp = 0; jp < 4; jp++) {
                        uint32_t b[4];
                        ldsm4t(b, smem_u32(smem + PS_W1 + krow * W_PITCH + (2 * jp + nsel) * 16));
                        if (q == 0) {
                            mma16816_z(a[2 * jp], af, b[0], b[1]);
                            mma16816_z(a[2 * jp + 1], af, b[2], b[3]);
                        } else {
                            mma16816(a[2 * jp], af, b[0], b[1]);
                            mma16816(a[2 * jp + 1], af, b[2], b[3]);
                        }
                    }
                }
#pragma unroll
                for (int j = 0; j < 8; j++) {
                    float f[4];
#pragma unroll
                    for (int e = 0; e < 4; e++) {
                        const float z = bf16r(a[j][e]);
                        f[e] = __fdividef(z, 1.0f + __expf(-z));
                    }
                    h[j >> 1][(j & 1) * 2 + 0] = pack_bf16(f[0], f[1]);
                    h[j >> 1][(j & 1) * 2 + 1] = pack_bf16(f[2], f[3]);
                }
            }
            r0[0] = make_uint4(h[0][0], h[0][2], h[1][0], h[1][2]);
            r0[1] = make_uint4(h[2][0], h[2][2], h[3][0], h[3][2]);
            r1[0] = make_uint4(h[0][1], h[0][3], h[1][1], h[1][3]);
            r1[1] = make_uint4(h[2][1], h[2][3], h[3][1], h[3][3]);
            float p[8][4];
            {
                const int i = lane & 15, nsel = lane >> 4;
#pragma unroll
                for (int q = 0; q < 4; q++) {
#pragma unroll
                    for (int jp = 0; jp < 4; jp++) {
                        uint32_t b[4];
                        ldsm4t(b, smem_u32(smem + PS_W2 + (16 * q + i) * W_PITCH + (2 * jp + nsel) * 16));
                        if (q == 0) {
                            mma16816_z(p[2 * jp], h[0], b[0], b[1]);
                            mma16816_z(p[2 * jp + 1], h[0], b[2], b[3]);
                        } else {
                            mma16816(p[2 * jp], h[q], b[0], b[1]);
                            mma16816(p[2 * jp + 1], h[q], b[2], b[3]);
                        }
                    }
                }
            }
#pragma unroll
            for (int r = 0; r < 2; r++) {
                uint4* row = r ? r1 : r0;
                uint32_t pv[8];
#pragma unroll
                for (int j = 0; j < 8; j++) pv[j] = pack_bf16(p[j][2 * r], p[j][2 * r + 1]);
#pragma unroll
                for (int c = 1; c < 4; c++) {
                    uint4 vx[2] = {row[c * 8], row[c * 8 + 1]};
                    const uint32_t* vv = reinterpret_cast<const uint32_t*>(vx);
                    uint32_t u[8];
#pragma unroll
                    for (int j = 0; j < 8; j++) u[j] = hmul2(pv[j], vv[j]);
                    row[c * 8] = make_uint4(__byte_perm(u[0], u[1], 0x5410), __byte_perm(u[2], u[3], 0x5410),
                                            __byte_perm(u[4], u[5], 0x5410), __byte_perm(u[6], u[7], 0x5410));
                    row[c * 8 + 1] = make_uint4(__byte_perm(u[0], u[1], 0x7632), __byte_perm(u[2], u[3], 0x7632),
                                                __byte_perm(u[4], u[5], 0x7632), __byte_perm(u[6], u[7], 0x7632));
                }
            }
            asm volatile("fence.proxy.async.shared::cta;" ::: "memory");
            __syncwarp();
            if (tid == 0) STAMP(3);
            if (lane == 0) {
                bulk_s2g(g_tab + (size_t)tile * 16 * ROWB, smem_u32(tb), nrows * 512);
                asm volatile("cp.async.bulk.commit_group;" ::: "memory");
                asm volatile("cp.async.bulk.wait_group 0;" ::: "memory");
            }
            if (tid == 0) STAMP(4);
        }
    } else {
        const int ptid = tid - 32 * P1_WARPS, pwarp = warp - P1_WARPS;
        const uint32_t bar = smem_u32(smem + PS_BAR);
        const int posbytes = N * 6;
        if (ptid == 0) {
            mbar_init(bar, 1);
            asm volatile("fence.mbarrier_init.release.cluster;" ::: "memory");
            mbar_expect_tx(bar, posbytes);
            bulk_g2s(smem_u32(smem + PS_POS), pos, posbytes, bar);
        }
        const int npairs = E >> 1;
        const int ppc = (npairs + NCTA - 1) / NCTA;
        const int pbeg = blockIdx.x * ppc, pend = min(pbeg + ppc, npairs);
        int2 es[P3_ITERS], ed[P3_ITERS];
#pragma unroll
        for (int it = 0; it < P3_ITERS; it++) {
            const int p = pbeg + ptid + it * P3_THREADS;
            if (p < pend) {
                es[it] = __ldcs(reinterpret_cast<const int2*>(src) + p);
                ed[it] = __ldcs(reinterpret_cast<const int2*>(dst) + p);
            }
        }
        int* hist = reinterpret_cast<int*>(smem + PS_HIST);
        for (int i = ptid; i < 1280; i += P3_THREADS) hist[i] = 0;
        {
            const int gi = ptid * NCTA + blockIdx.x;
            if (gi < NTAB * NRBF) {
                const int di = gi >> 4, k = gi & 15;
                const float d = __uint_as_float((uint32_t)(DBASE + di) << 16);
                const float arg = bf16r(d * __bfloat162float(freqs[k]));
                const float rbf = bf16r(bf16r(sinf(arg)) / d);
                const float ca = bf16r(bf16r(3.14159265358979f * d) / 5.0f);
                const float fc = 0.5f * bf16r(bf16r(cosf(ca)) + 1.0f);
                g_G[gi] = __float2bfloat16_rn(rbf * fc);
            }
        }
        if (ptid == 0) STAMP(5);
        asm volatile("bar.sync 2, %0;" ::"n"(P3_THREADS) : "memory");
        if (ptid == 0) STAMP(6);
        mbar_wait(bar, 0);
        if (ptid == 0) STAMP(7);
        const uint32_t* pw = reinterpret_cast<const uint32_t*>(smem + PS_POS);
        uint2 rec[P3_ITERS * 2];
        int key[P3_ITERS * 2];
#pragma unroll
        for (int q = 0; q < P3_ITERS * 2; q++) {
            const int it = q >> 1;
            key[q] = -1;
            if (pbeg + ptid + it * P3_THREADS < pend) {
                const int s = (q & 1) ? es[it].y : es[it].x;
                const int dd = (q & 1) ? ed[it].y : ed[it].x;
                const int ws = (s * 3) >> 1, wd = (dd * 3) >> 1;
                const uint32_t sa = pw[ws], sb = pw[ws + 1], da = pw[wd], db = pw[wd + 1];
                const uint32_t shs = (s & 1) << 4, shd = (dd & 1) << 4;
                const uint32_t rxy = hsub2(__funnelshift_r(sa, sb, shs), __funnelshift_r(da, db, shd));
                const uint32_t rz = hsub2(sb >> shs, db >> shd);
                const uint32_t qxy = hmul2(rxy, rxy), qz = hmul2(rz, rz);
                const float sum = (__uint_as_float(qxy << 16) + __uint_as_float(qxy & 0xffff0000u)) + __uint_as_float(qz << 16);
                if (sum < 23.9375f) {
                    const uint32_t exy = hmul2(rxy, 0x1e801e80u), ez = hmul2(rz, 0x1e801e80u);
                    rec[q].x = exy | ((dd & 3) << 13) | ((dd & 12) << 27);
                    rec[q].y = (ez & 0xffffu) | ((dd & 48) << 9) | ((uint32_t)s << 16) | ((uint32_t)(dd & 64) << 25);
                    const int grp = dd >> 3;
                    key[q] = (grp << 13) | atomicAdd(&hist[grp], 1);
                }
            }
        }
        if (ptid == 0) STAMP(8);
        asm volatile("bar.sync 2, %0;" ::"n"(P3_THREADS) : "memory");
        if (ptid == 0) STAMP(9);
        int2 hv = make_int2(0, 0);
        int incl = 0;
        if (pwarp < 20) {
            hv = reinterpret_cast<int2*>(hist)[ptid];
            incl = hv.x + hv.y;
#pragma unroll
            for (int o = 1; o < 32; o <<= 1) {
                const int v = __shfl_up_sync(0xffffffffu, incl, o);
                if (lane >= o) incl += v;
            }
            if (lane == 31) hist[1280 + pwarp] = incl;
        }
        asm volatile("bar.sync 2, %0;" ::"n"(P3_THREADS) : "memory");
        if (pwarp < 20) {
            int wsum = (lane < pwarp) ? hist[1280 + lane] : 0;
            wsum = __reduce_add_sync(0xffffffffu, wsum);
            const int ex = wsum + incl - hv.x - hv.y;
            reinterpret_cast<int2*>(hist)[ptid] = make_int2(ex, ex + hv.x);
        }
        asm volatile("bar.sync 2, %0;" ::"n"(P3_THREADS) : "memory");
        if (ptid == 0) STAMP(10);
        uint2* srec = reinterpret_cast<uint2*>(smem + PS_REC);
#pragma unroll
        for (int q = 0; q < P3_ITERS * 2; q++)
            if (key[q] >= 0) srec[hist[key[q] >> 13] + (key[q] & 8191)] = rec[q];
        const int ngroups = (N + GRP - 1) / GRP;
        unsigned short* spfx = reinterpret_cast<unsigned short*>(smem + PS_PFX);
        for (int i = ptid; i < NCTA * 16; i += P3_THREADS)
            spfx[i] = (unsigned short)hist[min(group_begin(i >> 4, ngroups) + (i & 15), ngroups)];
        asm volatile("fence.proxy.async.shared::cta;" ::: "memory");
        asm volatile("bar.sync 2, %0;" ::"n"(P3_THREADS) : "memory");
        if (ptid == 0) {
            STAMP(11);
            const int total = hist[ngroups];
            const int bytes = ((total + 1) >> 1) * 16;
            if (bytes > 0) bulk_s2g(g_rec + blockIdx.x * CH, smem_u32(srec), bytes);
            bulk_s2g(g_pfx + blockIdx.x * NCTA * 16, smem_u32(spfx), NCTA * 32);
            asm volatile("cp.async.bulk.commit_group;" ::: "memory");
            asm volatile("cp.async.bulk.wait_group 0;" ::: "memory");
            STAMP(12);
        }
    }
}

constexpr int UNITS = 3;
constexpr int STAGES = 3;
constexpr int M_THREADS = UNITS * 128 + 128;
constexpr int ST_G = 4 * 4096;
constexpr int ST_S = ST_G + 1024;
constexpr int STAGE_BYTES = ST_S + 2048;
constexpr int RCAP = 4736;
constexpr int MAXQ = 10;
constexpr int HOT0 = 0x3F00 - DBASE;
constexpr int MS_REC = UNITS * STAGES * STAGE_BYTES;
constexpr int MS_GH = MS_REC + RCAP * 8;
constexpr int MS_B2 = MS_GH + (NTAB - HOT0) * 32;
constexpr int MS_MISC = MS_B2 + MAXQ * 136 * 4;
constexpr int MS_BAR = MS_MISC + 32 * 4;
constexpr int M_SMEM = MS_BAR + (2 * UNITS * STAGES + 1) * 8;
static_assert(M_SMEM <= 232448, "smem");
static_assert(MS_BAR % 8 == 0 && MS_GH % 16 == 0 && STAGE_BYTES % 1024 == 0, "align");

__device__ __forceinline__ void wgmma_n32(float (&d)[16], const uint32_t (&a)[4], uint64_t desc, bool acc) {
    if (acc) {
        asm volatile("wgmma.mma_async.sync.aligned.m64n32k16.f32.bf16.bf16 {%0,%1,%2,%3,%4,%5,%6,%7,%8,%9,%10,%11,%12,%13,%14,%15}, {%16,%17,%18,%19}, %20, 1, 1, 1, 0;\n"
                     : "+f"(d[0]), "+f"(d[1]), "+f"(d[2]), "+f"(d[3]), "+f"(d[4]), "+f"(d[5]), "+f"(d[6]), "+f"(d[7]),
                       "+f"(d[8]), "+f"(d[9]), "+f"(d[10]), "+f"(d[11]), "+f"(d[12]), "+f"(d[13]), "+f"(d[14]), "+f"(d[15])
                     : "r"(a[0]), "r"(a[1]), "r"(a[2]), "r"(a[3]), "l"(desc));
    } else {
        asm volatile("wgmma.mma_async.sync.aligned.m64n32k16.f32.bf16.bf16 {%0,%1,%2,%3,%4,%5,%6,%7,%8,%9,%10,%11,%12,%13,%14,%15}, {%16,%17,%18,%19}, %20, 0, 1, 1, 0;\n"
                     : "=f"(d[0]), "=f"(d[1]), "=f"(d[2]), "=f"(d[3]), "=f"(d[4]), "=f"(d[5]), "=f"(d[6]), "=f"(d[7]),
                       "=f"(d[8]), "=f"(d[9]), "=f"(d[10]), "=f"(d[11]), "=f"(d[12]), "=f"(d[13]), "=f"(d[14]), "=f"(d[15])
                     : "r"(a[0]), "r"(a[1]), "r"(a[2]), "r"(a[3]), "l"(desc));
    }
}
__device__ __forceinline__ void reg_fence16(float (&d)[16]) {
    asm volatile("" : "+f"(d[0]), "+f"(d[1]), "+f"(d[2]), "+f"(d[3]), "+f"(d[4]), "+f"(d[5]), "+f"(d[6]), "+f"(d[7]),
                      "+f"(d[8]), "+f"(d[9]), "+f"(d[10]), "+f"(d[11]), "+f"(d[12]), "+f"(d[13]), "+f"(d[14]), "+f"(d[15]) :: "memory");
}
__device__ __forceinline__ uint32_t opaque(uint32_t x) { asm volatile("" : "+r"(x)); return x; }

__global__ void __launch_bounds__(M_THREADS, 1)
main_kernel(const __nv_bfloat16* __restrict__ sv, const __nv_bfloat16* __restrict__ w2,
            const __nv_bfloat16* __restrict__ wrbf, __nv_bfloat16* __restrict__ out, int N) {
    extern __shared__ __align__(1024) unsigned char smem[];
    const int tid = threadIdx.x, warp = tid >> 5, lane = tid & 31;
    const int g = lane >> 2, t = lane & 3;
    const int ngroups = (N + GRP - 1) / GRP;
    const int q0 = group_begin(blockIdx.x, ngroups);
    const int nq = group_begin(blockIdx.x + 1, ngroups) - q0;
    const uint32_t sbase = smem_u32(smem);
    const uint32_t ghbar = sbase + MS_BAR + 2 * UNITS * STAGES * 8;
    int* misc = reinterpret_cast<int*>(smem + MS_MISC);
    const bool is_prod = warp >= UNITS * 4;

    if (tid == 0) {
        STAMP(16);
        for (int i = 0; i < UNITS * STAGES; i++) {
            mbar_init(sbase + MS_BAR + i * 16, 33);
            mbar_init(sbase + MS_BAR + i * 16 + 8, 4);
        }
        mbar_init(ghbar, 1);
        asm volatile("fence.mbarrier_init.release.cluster;" ::: "memory");
        misc[16] = UNITS;
    }
    if (tid == 0) STAMP(17);
    asm volatile("griddepcontrol.wait;" ::: "memory");
    if (tid == 0) STAMP(18);

    const unsigned short* pfx = g_pfx + blockIdx.x * 16;
    int* b2 = reinterpret_cast<int*>(smem + MS_B2);
    uint2* srec = reinterpret_cast<uint2*>(smem + MS_REC);
    {
        if (tid == 0) {
            mbar_expect_tx(ghbar, (NTAB - HOT0) * 32);
            bulk_g2s(sbase + MS_GH, g_G + HOT0 * NRBF, (NTAB - HOT0) * 32, ghbar);
        }
        int beg = 0, end = 0;
        {
            const int p = warp + 16 * lane;
            if (p < NCTA) {
                beg = __ldcg(pfx + p * NCTA * 16);
                end = __ldcg(pfx + p * NCTA * 16 + nq);
            }
        }
        int lo[5], cq[5];
        if (warp < nq) {
#pragma unroll
            for (int k = 0; k < 5; k++) {
                const int p = lane * 5 + k;
                lo[k] = 0; cq[k] = 0;
                if (p < NCTA) {
                    lo[k] = __ldcg(pfx + p * NCTA * 16 + warp);
                    cq[k] = __ldcg(pfx + p * NCTA * 16 + warp + 1);
                }
            }
        }
        uint2 r[9];
#pragma unroll
        for (int k = 0; k < 9; k++) {
            const int i = __shfl_sync(0xffffffffu, beg, k) + lane;
            const int e = __shfl_sync(0xffffffffu, end, k);
            if (i < e) r[k] = __ldcg(g_rec + (warp + 16 * k) * CH + i);
        }
        int pre = 0;
        if (warp < nq) {
            int sum = 0;
#pragma unroll
            for (int k = 0; k < 5; k++) { cq[k] -= lo[k]; sum += cq[k]; }
            int in2 = sum;
#pragma unroll
            for (int o = 1; o < 32; o <<= 1) {
                const int v = __shfl_up_sync(0xffffffffu, in2, o);
                if (lane >= o) in2 += v;
            }
            pre = in2 - sum;
            if (lane == 31) misc[warp] = in2;
        }
        __syncthreads();
        if (tid == 0) STAMP(19);
        const int tv = lane < nq ? misc[lane] : 0;
        const bool fits = __reduce_add_sync(0xffffffffu, tv) <= RCAP;
        if (warp < nq) {
            if (fits) pre += __reduce_add_sync(0xffffffffu, lane < warp ? tv : 0);
#pragma unroll
            for (int k = 0; k < 5; k++) {
                const int p = lane * 5 + k;
                if (p < NCTA) b2[warp * 136 + p] = fits ? pre - lo[k] : pre;
                pre += cq[k];
            }
        }
        __syncthreads();
        if (fits) {
#pragma unroll
            for (int k = 0; k < 9; k++) {
                const int p = warp + 16 * k;
                int i = __shfl_sync(0xffffffffu, beg, k) + lane;
                const int e = __shfl_sync(0xffffffffu, end, k);
                uint2 v = r[k];
                while (i < e) {
                    const int q = (int)((((v.x >> 30) & 1u) | ((v.y >> 12) & 6u) | ((v.y >> 28) & 8u)) - (uint32_t)q0) & 15;
                    srec[b2[q * 136 + p] + i] = v;
                    i += 32;
                    if (i < e) v = __ldcg(g_rec + p * CH + i);
                }
            }
        }
        if (tid == 0) misc[17] = fits;
        __syncthreads();
    }
    if (tid == 0) STAMP(20);

    if (is_prod) {
        asm volatile("setmaxnreg.dec.sync.aligned.u32 56;");
        const int unit = warp - UNITS * 4;
        const uint32_t ubase = sbase + unit * STAGES * STAGE_BYTES;
        const uint32_t ubar = sbase + MS_BAR + unit * STAGES * 16;
        const uint32_t uflag = sbase + MS_MISC + (20 + unit * STAGES) * 4;
        if (unit < UNITS) {
            const bool fits = misc[17] != 0;
            mbar_wait(ghbar, 0);
            if (unit == 0 && lane == 0) STAMP(21);
            const unsigned char* gsrc = g_tab + (lane & 7) * 16;
            const int r4 = lane >> 3;
            const uint32_t d0 = r4 * 128 + (((lane & 7) ^ r4) << 4);
            const uint32_t d1 = (r4 + 4) * 128 + (((lane & 7) ^ (r4 + 4)) << 4);
            const uint32_t goff = ST_G + lane * 32 + (((lane >> 2) & 1) << 4);
            int st = 0, ph = 1;
            int q = unit;
            while (q < nq) {
                int base = (lane < q) ? misc[lane] : 0;
                base = __reduce_add_sync(0xffffffffu, base) + lane;
                const int cnt = misc[q];
                int rem = cnt;
                const int grp = q0 + q;
                bool last;
                do {
                    const bool valid = lane < rem;
                    last = rem <= 24;
                    uint2 r = make_uint2(0, 0);
                    if (fits) {
                        if (valid) r = srec[base];
                    } else if (valid) {
                        const int j = cnt - rem + lane;
                        const int* prq = b2 + q * 136;
                        int lo = 0, hi = NCTA;
                        while (hi - lo > 1) {
                            const int mid = (lo + hi) >> 1;
                            if (prq[mid] <= j) lo = mid; else hi = mid;
                        }
                        r = __ldcg(g_rec + lo * CH + __ldcg(pfx + lo * NCTA * 16 + q) + (j - prq[lo]));
                    }
                    base += 32;
                    const uint32_t rxy = hmul2(r.x & 0x9fff9fffu, 0x60806080u);
                    const uint32_t rz2 = hmul2(r.y & 0x00009fffu, 0x60806080u);
                    const uint32_t qxy = hmul2(rxy, rxy), qz = hmul2(rz2, rz2);
                    const float sum = bf16r((__uint_as_float(qxy << 16) + __uint_as_float(qxy & 0xffff0000u)) + __uint_as_float(qz << 16));
                    float sq;
                    asm("sqrt.approx.ftz.f32 %0, %1;" : "=f"(sq) : "f"(bf16r(sum + 1e-8f)));
                    const uint32_t dbits = pack_bf16(0.f, sq);
                    float rinv;
                    asm("rcp.approx.ftz.f32 %0, %1;" : "=f"(rinv) : "f"(__uint_as_float(dbits)));
                    const int di = min(max((int)(dbits >> 16) - DBASE, 0), NTAB - 1);
                    const uint4* gp = (di >= HOT0) ? reinterpret_cast<const uint4*>(smem + MS_GH - HOT0 * 32) + 2 * di
                                                   : reinterpret_cast<const uint4*>(g_G) + 2 * di;
                    uint4 g0 = make_uint4(0, 0, 0, 0), g1 = g0;
                    if (valid) { g0 = gp[0]; g1 = gp[1]; }
                    const uint32_t r01 = pack_bf16(__uint_as_float(rxy << 16) * rinv, __uint_as_float(rxy & 0xffff0000u) * rinv);
                    const uint32_t r2 = pack_bf16(__uint_as_float(rz2 << 16) * rinv, valid ? 1.0f : 0.f);
                    const uint32_t soff = ST_S + lane * 16 + (((r.x >> 12) & 6u) | ((r.x >> 26) & 8u));
                    const uint32_t srcv = (r.y >> 16) & 0x7fffu;

                    mbar_wait(ubar + st * 16 + 8, ph);
                    const uint32_t sb = ubase + st * STAGE_BYTES;
#pragma unroll
                    for (int k = 0; k < 8; k++) {
                        const int e = k * 4 + r4;
                        const uint32_t s = __shfl_sync(0xffffffffu, srcv, e);
                        const unsigned char* gq = gsrc + (size_t)s * ROWB;
                        int lim = rem;
                        if (k >= 6 && last) {
                            const int node = grp * GRP + e - 24;
                            gq = reinterpret_cast<const unsigned char*>(sv) + (size_t)node * 512 + (lane & 7) * 16;
                            lim = node < N ? 32 : 0;
                        }
                        const uint32_t dp = sb + ((k & 1) ? d1 : d0) + (k >> 1) * 1024;
                        asm volatile("{\n.reg .pred p;\nsetp.ge.s32 p, %2, %3;\n"
                                     "cp.async.cg.shared.global [%0], [%1], 16, p;\n"
                                     "cp.async.cg.shared.global [%0+4096], [%1+128], 16, p;\n"
                                     "cp.async.cg.shared.global [%0+8192], [%1+256], 16, p;\n"
                                     "cp.async.cg.shared.global [%0+12288], [%1+384], 16, p;\n}\n"
                                     ::"r"(dp), "l"(gq), "r"(e), "r"(lim) : "memory");
                    }
                    asm volatile("cp.async.mbarrier.arrive.noinc.shared::cta.b64 [%0];" ::"r"(ubar + st * 16) : "memory");
#pragma unroll
                    for (int j = 0; j < 4; j++)
                        asm volatile("st.shared.v4.u32 [%0], {%1,%1,%1,%1};" ::"r"(sb + ST_S + lane * 16 + j * 512), "r"(0u) : "memory");
                    asm volatile("st.shared.u16 [%0], %1;" ::"r"(sb + soff), "h"((unsigned short)(r2 >> 16)) : "memory");
                    asm volatile("st.shared.u16 [%0], %1;" ::"r"(sb + soff + 512), "h"((unsigned short)(r01 & 0xffffu)) : "memory");
                    asm volatile("st.shared.u16 [%0], %1;" ::"r"(sb + soff + 1024), "h"((unsigned short)(r01 >> 16)) : "memory");
                    asm volatile("st.shared.u16 [%0], %1;" ::"r"(sb + soff + 1536), "h"((unsigned short)(r2 & 0xffffu)) : "memory");
                    asm volatile("st.shared.v4.u32 [%0], {%1,%2,%3,%4};" ::"r"(sb + goff),
                                 "r"(g0.x), "r"(g0.y), "r"(g0.z), "r"(g0.w) : "memory");
                    asm volatile("st.shared.v4.u32 [%0], {%1,%2,%3,%4};" ::"r"((sb + goff) ^ 16u),
                                 "r"(g1.x), "r"(g1.y), "r"(g1.z), "r"(g1.w) : "memory");
                    asm volatile("st.shared.u32 [%0], %1;" ::"r"(uflag + st * 4),
                                 "r"(((uint32_t)grp << 4) | (last ? 2u : 0u) | (rem > 0 ? 1u : 0u)) : "memory");
                    __syncwarp();
                    if (lane == 0) mbar_arrive(ubar + st * 16);
                    if (++st == STAGES) { st = 0; ph ^= 1; }
                    rem -= 32;
                } while (!last);
                int nx = 0;
                if (lane == 0) nx = atomicAdd(&misc[16], 1);
                q = __shfl_sync(0xffffffffu, nx, 0);
            }
            mbar_wait(ubar + st * 16 + 8, ph);
            asm volatile("st.shared.u32 [%0], %1;" ::"r"(uflag + st * 4), "r"(8u) : "memory");
            __syncwarp();
            mbar_arrive(ubar + st * 16);
            if (lane == 0) mbar_arrive(ubar + st * 16);
            if (lane == 0) STAMP(22 + unit);
        }
    } else {
        asm volatile("setmaxnreg.inc.sync.aligned.u32 152;");
        const int unit = warp >> 2, w = warp & 3;
        const uint32_t ubase = sbase + unit * STAGES * STAGE_BYTES;
        const uint32_t ubar = sbase + MS_BAR + unit * STAGES * 16;
        const uint32_t uflag = sbase + MS_MISC + (20 + unit * STAGES) * 4;
        uint32_t wa[3][4], pa[2][4][4];
        {
            const int c = 16 * w + 2 * g;
#pragma unroll
            for (int p = 0; p < 3; p++)
#pragma unroll
                for (int kh = 0; kh < 2; kh++) {
                    const uint32_t lo = __ldg(reinterpret_cast<const uint32_t*>(wrbf + (2 * t + 8 * kh) * 192 + p * 64 + c));
                    const uint32_t hi = __ldg(reinterpret_cast<const uint32_t*>(wrbf + (2 * t + 8 * kh + 1) * 192 + p * 64 + c));
                    wa[p][2 * kh + 0] = __byte_perm(lo, hi, 0x5410);
                    wa[p][2 * kh + 1] = __byte_perm(lo, hi, 0x7632);
                }
#pragma unroll
            for (int p = 0; p < 2; p++)
#pragma unroll
                for (int q = 0; q < 4; q++)
#pragma unroll
                    for (int kh = 0; kh < 2; kh++) {
                        const int r = 8 * (t + 4 * kh) + 2 * q;
                        const uint32_t lo = __ldg(reinterpret_cast<const uint32_t*>(w2 + r * 192 + p * 128 + c));
                        const uint32_t hi = __ldg(reinterpret_cast<const uint32_t*>(w2 + (r + 1) * 192 + p * 128 + c));
                        pa[p][q][2 * kh + 0] = __byte_perm(lo, hi, 0x5410);
                        pa[p][q][2 * kh + 1] = __byte_perm(lo, hi, 0x7632);
                    }
        }
        float acc[4][4];
#pragma unroll
        for (int c = 0; c < 4; c++)
#pragma unroll
            for (int e = 0; e < 4; e++) acc[c][e] = 0.f;
        const int erow = (lane & 7) + 8 * (lane >> 4);
        const int ehalf = (lane >> 3) & 1;
        const uint32_t ua = opaque(4096 + erow * 128 + ((uint32_t)((2 * w + ehalf) ^ (lane & 7)) << 4));
        const uint32_t sa = opaque(ST_S + lane * 16);
        const uint32_t ub = __shfl_sync(0xffffffffu, ubase, 0);
        uint32_t sb = ub, bar = ubar, flg = uflag;
        uint32_t ph = 0;
        while (true) {
            mbar_wait(bar, ph);
            uint32_t flags;
            asm volatile("ld.shared.u32 %0, [%1];" : "=r"(flags) : "r"(flg));
            if (flags & 1u) {
                asm volatile("fence.proxy.async.shared::cta;" ::: "memory");
                const uint32_t dlo = (sb & 0x3FFFFu) >> 4;
                const uint64_t dh = (uint64_t)(dlo | (1u << 16)) | ((uint64_t)(64u | (1u << 30)) << 32);
                const uint64_t dg = (uint64_t)((dlo + (ST_G >> 4)) | (1u << 16)) | ((uint64_t)(16u | (3u << 30)) << 32);
                uint32_t m[2][4], wv[2][4], sf[4];
                {
                    float ps[16], fs[16], fv[16];
                    asm volatile("wgmma.fence.sync.aligned;" ::: "memory");
                    wgmma_n32(fv, wa[1], dg, false);
                    wgmma_n32(fs, wa[0], dg, false);
#pragma unroll
                    for (int q = 0; q < 4; q++) wgmma_n32(ps, pa[0][q], dh + 2 * q, q > 0);
                    asm volatile("wgmma.commit_group.sync.aligned;" ::: "memory");
                    ldsm4t(sf, sb + sa);
                    asm volatile("wgmma.wait_group.sync.aligned 0;" ::: "memory");
                    reg_fence16(fv); reg_fence16(fs); reg_fence16(ps);
#pragma unroll
                    for (int i = 0; i < 8; i++) {
                        m[i >> 2][i & 3] = pack_bf16(fs[2 * i] * ps[2 * i], fs[2 * i + 1] * ps[2 * i + 1]);
                        wv[i >> 2][i & 3] = pack_bf16(fv[2 * i], fv[2 * i + 1]);
                    }
                }
                float pr[16], fr[16];
                asm volatile("wgmma.fence.sync.aligned;" ::: "memory");
                wgmma_n32(fr, wa[2], dg, false);
#pragma unroll
                for (int q = 0; q < 4; q++) wgmma_n32(pr, pa[1][q], dh + 2 * q, q > 0);
                asm volatile("wgmma.commit_group.sync.aligned;" ::: "memory");
#pragma unroll
                for (int s = 0; s < 2; s++) {
                    mma16816(acc[0], m[s], sf[2 * s], sf[2 * s + 1]);
#pragma unroll
                    for (int j = 0; j < 3; j++) {
                        uint32_t x[4];
                        ldsm4t(x, sb + ua + j * 4096 + s * 2048);
#pragma unroll
                        for (int e = 0; e < 4; e++) x[e] = hmul2(x[e], wv[s][e]);
                        mma16816(acc[j + 1], x, sf[2 * s], sf[2 * s + 1]);
                    }
                }
                uint32_t sj[3][4];
#pragma unroll
                for (int j = 0; j < 3; j++) ldsm4t(sj[j], sb + sa + (j + 1) * 512);
                asm volatile("wgmma.wait_group.sync.aligned 0;" ::: "memory");
                reg_fence16(fr); reg_fence16(pr);
#pragma unroll
                for (int i = 0; i < 8; i++)
                    m[i >> 2][i & 3] = pack_bf16(fr[2 * i] * pr[2 * i], fr[2 * i + 1] * pr[2 * i + 1]);
#pragma unroll
                for (int s = 0; s < 2; s++)
#pragma unroll
                    for (int j = 0; j < 3; j++) mma16816(acc[j + 1], m[s], sj[j][2 * s], sj[j][2 * s + 1]);
            } else if (flags & 8u) {
                break;
            }
            if (flags & 2u) {
                const int node0 = (int)(flags >> 4) * GRP + 2 * t;
                uint32_t* op = reinterpret_cast<uint32_t*>(out) + (size_t)node0 * 128 + 8 * w + g;
#pragma unroll
                for (int b = 0; b < 2; b++) {
                    const uint32_t va = sb + (24 + 2 * t + b) * 128 + (((uint32_t)(2 * w + (g >> 2)) ^ (uint32_t)(2 * t + b)) << 4) + (g & 3) * 4;
#pragma unroll
                    for (int c = 0; c < 4; c++) {
                        uint32_t v;
                        asm volatile("ld.shared.u32 %0, [%1];" : "=r"(v) : "r"(va + c * 4096));
                        const uint32_t o = pack_bf16(__uint_as_float(v << 16) + acc[c][b],
                                                     __uint_as_float(v & 0xffff0000u) + acc[c][2 + b]);
                        if (node0 + b < N) op[b * 128 + c * 32] = o;
                        acc[c][b] = 0.f; acc[c][2 + b] = 0.f;
                    }
                }
            }
            __syncwarp();
            if (lane == 0) mbar_arrive(bar + 8);
            sb += STAGE_BYTES; bar += 16; flg += 4;
            if (sb == ub + STAGES * STAGE_BYTES) { sb = ub; bar -= STAGES * 16; flg -= STAGES * 4; ph ^= 1; }
        }
        if (lane == 0 && w == 0) STAMP(26 + unit);
    }
}

}

extern "C" void kernel_launch(void* const* d_in, const int* in_sizes, int n_in, void* d_out, int out_size) {
    const __nv_bfloat16* sv = (const __nv_bfloat16*)d_in[0];
    const __nv_bfloat16* pos = (const __nv_bfloat16*)d_in[1];
    const int* src = (const int*)d_in[2];
    const int* dst = (const int*)d_in[3];
    const __nv_bfloat16* freqs = (const __nv_bfloat16*)d_in[4];
    const __nv_bfloat16* w1 = (const __nv_bfloat16*)d_in[5];
    const __nv_bfloat16* w2 = (const __nv_bfloat16*)d_in[6];
    const __nv_bfloat16* wrbf = (const __nv_bfloat16*)d_in[7];
    __nv_bfloat16* out = (__nv_bfloat16*)d_out;
    const int N = in_sizes[1] / 3;
    const int E = in_sizes[2];

    static bool init = false;
    if (!init) {
        cudaFuncSetAttribute(prep_kernel, cudaFuncAttributeMaxDynamicSharedMemorySize, PS_TOTAL);
        cudaFuncSetAttribute(main_kernel, cudaFuncAttributeMaxDynamicSharedMemorySize, M_SMEM);
        init = true;
    }
    cudaStream_t stream = cudaStreamPerThread;
    prep_kernel<<<NCTA, P_THREADS, PS_TOTAL, stream>>>(sv, pos, src, dst, freqs, w1, w2, N, E);

    cudaLaunchConfig_t cfg = {};
    cfg.gridDim = dim3(NCTA);
    cfg.blockDim = dim3(M_THREADS);
    cfg.dynamicSmemBytes = M_SMEM;
    cfg.stream = stream;
    cudaLaunchAttribute at[1];
    at[0].id = cudaLaunchAttributeProgrammaticStreamSerialization;
    at[0].val.programmaticStreamSerializationAllowed = 1;
    cfg.attrs = at;
    cfg.numAttrs = 1;
    cudaLaunchKernelEx(&cfg, main_kernel, sv, w2, wrbf, out, N);
}
```

```cpp
#include <cuda_runtime.h>
#include <cuda_bf16.h>
#include <stdint.h>

namespace {

constexpr int D = 64;
constexpr int NRBF = 16;
constexpr int MAXN = 10000;
constexpr int MAXE = 640000;
constexpr int NCTA = 132;
constexpr int GRP = 8;
constexpr int MAXG = (MAXN + GRP - 1) / GRP;
constexpr int CH = 4864;
constexpr int DBASE = 0x38C0;
constexpr int DEND = 0x40A0;
constexpr int NTAB = DEND - DBASE;
constexpr int ROWB = 512;

__device__ __align__(128) unsigned char g_tab[(size_t)(MAXN + 16) * ROWB];
__device__ __align__(128) __nv_bfloat16 g_G[NTAB * NRBF];
__device__ __align__(128) uint2 g_rec[NCTA * CH];
__device__ __align__(128) unsigned short g_pfx[NCTA * NCTA * 16];

#define STAMP(k) do {} while (0)

__device__ __forceinline__ uint32_t smem_u32(const void* p) { return (uint32_t)__cvta_generic_to_shared(p); }
__device__ __forceinline__ uint32_t pack_bf16(float lo, float hi) {
    uint32_t r;
    asm("cvt.rn.bf16x2.f32 %0, %1, %2;" : "=r"(r) : "f"(hi), "f"(lo));
    return r;
}
__device__ __forceinline__ float bf16r(float x) { return __uint_as_float(pack_bf16(0.f, x) & 0xffff0000u); }
__device__ __forceinline__ uint32_t hmul2(uint32_t a, uint32_t b) {
    uint32_t r;
    asm("mul.rn.bf16x2 %0, %1, %2;" : "=r"(r) : "r"(a), "r"(b));
    return r;
}
__device__ __forceinline__ uint32_t hsub2(uint32_t a, uint32_t b) {
    uint32_t r;
    asm("sub.rn.bf16x2 %0, %1, %2;" : "=r"(r) : "r"(a), "r"(b));
    return r;
}
__device__ __forceinline__ uint32_t hfma2(uint32_t a, uint32_t b, uint32_t c) {
    uint32_t r;
    asm("fma.rn.bf16x2 %0, %1, %2, %3;" : "=r"(r) : "r"(a), "r"(b), "r"(c));
    return r;
}
__device__ __forceinline__ void mma16816(float (&c)[4], const uint32_t (&a)[4], uint32_t b0, uint32_t b1) {
    asm volatile("mma.sync.aligned.m16n8k16.row.col.f32.bf16.bf16.f32 {%0,%1,%2,%3}, {%4,%5,%6,%7}, {%8,%9}, {%0,%1,%2,%3};"
                 : "+f"(c[0]), "+f"(c[1]), "+f"(c[2]), "+f"(c[3])
                 : "r"(a[0]), "r"(a[1]), "r"(a[2]), "r"(a[3]), "r"(b0), "r"(b1));
}
__device__ __forceinline__ void mma16816_z(float (&c)[4], const uint32_t (&a)[4], uint32_t b0, uint32_t b1) {
    asm volatile("mma.sync.aligned.m16n8k16.row.col.f32.bf16.bf16.f32 {%0,%1,%2,%3}, {%4,%5,%6,%7}, {%8,%9}, {%10,%10,%10,%10};"
                 : "=f"(c[0]), "=f"(c[1]), "=f"(c[2]), "=f"(c[3])
                 : "r"(a[0]), "r"(a[1]), "r"(a[2]), "r"(a[3]), "r"(b0), "r"(b1), "f"(0.f));
}
__device__ __forceinline__ void ldsm4(uint32_t (&r)[4], uint32_t addr) {
    asm volatile("ldmatrix.sync.aligned.m8n8.x4.shared.b16 {%0,%1,%2,%3}, [%4];"
                 : "=r"(r[0]), "=r"(r[1]), "=r"(r[2]), "=r"(r[3]) : "r"(addr));
}
__device__ __forceinline__ void ldsm4t(uint32_t (&r)[4], uint32_t addr) {
    asm volatile("ldmatrix.sync.aligned.m8n8.x4.trans.shared.b16 {%0,%1,%2,%3}, [%4];"
                 : "=r"(r[0]), "=r"(r[1]), "=r"(r[2]), "=r"(r[3]) : "r"(addr));
}
__device__ __forceinline__ void mbar_init(uint32_t bar, int cnt) {
    asm volatile("mbarrier.init.shared::cta.b64 [%0], %1;" ::"r"(bar), "r"(cnt) : "memory");
}
__device__ __forceinline__ void mbar_arrive(uint32_t bar) {
    asm volatile("mbarrier.arrive.shared::cta.b64 _, [%0];" ::"r"(bar) : "memory");
}
__device__ __forceinline__ void mbar_expect_tx(uint32_t bar, uint32_t bytes) {
    asm volatile("mbarrier.arrive.expect_tx.shared::cta.b64 _, [%0], %1;" ::"r"(bar), "r"(bytes) : "memory");
}
__device__ __forceinline__ void mbar_wait(uint32_t bar, uint32_t parity) {
    asm volatile(
        "{\n.reg .pred p;\n.reg .u32 n;\nmov.u32 n, 0;\n"
        "WAIT_%=:\n"
        "mbarrier.try_wait.parity.shared::cta.b64 p, [%0], %1, %2;\n"
        "@p bra DONE_%=;\n"
        "add.u32 n, n, 1;\n"
        "setp.lt.u32 p, n, 100000;\n"
        "@p bra WAIT_%=;\n"
        "exit;\n"
        "DONE_%=:\n}\n" ::"r"(bar), "r"(parity), "r"(10000u) : "memory");
}
__device__ __forceinline__ void bulk_g2s(uint32_t dst, const void* src, uint32_t bytes, uint32_t bar) {
    asm volatile("cp.async.bulk.shared::cluster.global.mbarrier::complete_tx::bytes [%0], [%1], %2, [%3];"
                 ::"r"(dst), "l"(src), "r"(bytes), "r"(bar) : "memory");
}
__device__ __forceinline__ void bulk_s2g(void* dst, uint32_t src, uint32_t bytes) {
    asm volatile("cp.async.bulk.global.shared::cta.bulk_group [%0], [%1], %2;" ::"l"(dst), "r"(src), "r"(bytes) : "memory");
}
__device__ __forceinline__ int group_begin(int c, int ngroups) { return (c * ngroups) / NCTA; }

constexpr int P_THREADS = 1024;
constexpr int P1_WARPS = 5;
constexpr int P3_THREADS = P_THREADS - 32 * P1_WARPS;
constexpr int P3_ITERS = 3;
constexpr int W_PITCH = 144;
constexpr int PS_TILE = 0;
constexpr int PS_REC = PS_TILE + P1_WARPS * 8192;
constexpr int PS_PFX = PS_REC + CH * 8;
constexpr int PS_POS = PS_PFX + NCTA * 32;
constexpr int PS_W1 = PS_POS + 60032;
constexpr int PS_W2 = PS_W1 + 64 * W_PITCH;
constexpr int PS_HIST = PS_W2 + 64 * W_PITCH;
constexpr int PS_BAR = PS_HIST + (1280 + 32) * 4;
constexpr int PS_TOTAL = PS_BAR + 64;

__global__ void __launch_bounds__(P_THREADS, 1)
prep_kernel(const __nv_bfloat16* __restrict__ sv, const __nv_bfloat16* __restrict__ pos,
            const int* __restrict__ src, const int* __restrict__ dst,
            const __nv_bfloat16* __restrict__ freqs, const __nv_bfloat16* __restrict__ w1,
            const __nv_bfloat16* __restrict__ w2, int N, int E) {
    extern __shared__ __align__(1024) unsigned char smem[];
    const int tid = threadIdx.x, warp = tid >> 5, lane = tid & 31;
    asm volatile("griddepcontrol.launch_dependents;");
    if (tid == 0) STAMP(0);

    if (warp < P1_WARPS) {
        const int g = lane >> 2, t = lane & 3;
        const int tile = warp * gridDim.x + blockIdx.x;
        const int nrows = min(16, N - tile * 16);
        const uint32_t bar = smem_u32(smem + PS_BAR + 8 + 8 * warp);
        unsigned char* tb = smem + PS_TILE + warp * 8192;
        if (nrows > 0 && lane == 0) {
            mbar_init(bar, 1);
            asm volatile("fence.mbarrier_init.release.cluster;" ::: "memory");
            mbar_expect_tx(bar, nrows * 512);
            bulk_g2s(smem_u32(tb), sv + (size_t)tile * 16 * 256, nrows * 512, bar);
        }
        for (int i = tid; i < 64 * 8; i += 32 * P1_WARPS) {
            const int r = i >> 3, c = i & 7;
            *reinterpret_cast<uint4*>(smem + PS_W1 + r * W_PITCH + c * 16) =
                __ldg(reinterpret_cast<const uint4*>(w1 + r * 64) + c);
            const uint4 v = __ldg(reinterpret_cast<const uint4*>(w2 + r * 192 + 64) + c);
            const int tt = c >> 1, j0 = (c & 1) * 4;
            uint32_t* o = reinterpret_cast<uint32_t*>(smem + PS_W2 + r * W_PITCH);
            o[4 * (j0 + 0) + tt] = v.x; o[4 * (j0 + 1) + tt] = v.y;
            o[4 * (j0 + 2) + tt] = v.z; o[4 * (j0 + 3) + tt] = v.w;
        }
        asm volatile("bar.sync 1, %0;" ::"n"(32 * P1_WARPS) : "memory");
        if (tid == 0) STAMP(1);
        if (nrows > 0) {
            mbar_wait(bar, 0);
            if (tid == 0) STAMP(2);
            uint4* r0 = reinterpret_cast<uint4*>(tb + g * 512 + t * 32);
            uint4* r1 = reinterpret_cast<uint4*>(tb + (g + 8) * 512 + t * 32);
            uint32_t h[4][4];
            {
                uint4 xa[2] = {r0[0], r0[1]}, xb[2] = {r1[0], r1[1]};
                const uint32_t* s0 = reinterpret_cast<const uint32_t*>(xa);
                const uint32_t* s1 = reinterpret_cast<const uint32_t*>(xb);
                float a[8][4];
                const int i = lane & 7, hi = (lane >> 3) & 1, nsel = lane >> 4;
#pragma unroll
                for (int q = 0; q < 4; q++) {
                    const int krow = 16 * (i >> 1) + 4 * q + (i & 1) + 2 * hi;
                    const uint32_t af[4] = {s0[2 * q], s1[2 * q], s0[2 * q + 1], s1[2 * q + 1]};
#pragma unroll
                    for (int jp = 0; jp < 4; jp++) {
                        uint32_t b[4];
                        ldsm4t(b, smem_u32(smem + PS_W1 + krow * W_PITCH + (2 * jp + nsel) * 16));
                        if (q == 0) {
                            mma16816_z(a[2 * jp], af, b[0], b[1]);
                            mma16816_z(a[2 * jp + 1], af, b[2], b[3]);
                        } else {
                            mma16816(a[2 * jp], af, b[0], b[1]);
                            mma16816(a[2 * jp + 1], af, b[2], b[3]);
                        }
                    }
                }
#pragma unroll
                for (int j = 0; j < 8; j++) {
                    float f[4];
#pragma unroll
                    for (int e = 0; e < 4; e++) {
                        const float z = bf16r(a[j][e]);
                        f[e] = __fdividef(z, 1.0f + __expf(-z));
                    }
                    h[j >> 1][(j & 1) * 2 + 0] = pack_bf16(f[0], f[1]);
                    h[j >> 1][(j & 1) * 2 + 1] = pack_bf16(f[2], f[3]);
                }
            }
            r0[0] = make_uint4(h[0][0], h[0][2], h[1][0], h[1][2]);
            r0[1] = make_uint4(h[2][0], h[2][2], h[3][0], h[3][2]);
            r1[0] = make_uint4(h[0][1], h[0][3], h[1][1], h[1][3]);
            r1[1] = make_uint4(h[2][1], h[2][3], h[3][1], h[3][3]);
            float p[8][4];
            {
                const int i = lane & 15, nsel = lane >> 4;
#pragma unroll
                for (int q = 0; q < 4; q++) {
#pragma unroll
                    for (int jp = 0; jp < 4; jp++) {
                        uint32_t b[4];
                        ldsm4t(b, smem_u32(smem + PS_W2 + (16 * q + i) * W_PITCH + (2 * jp + nsel) * 16));
                        if (q == 0) {
                            mma16816_z(p[2 * jp], h[0], b[0], b[1]);
                            mma16816_z(p[2 * jp + 1], h[0], b[2], b[3]);
                        } else {
                            mma16816(p[2 * jp], h[q], b[0], b[1]);
                            mma16816(p[2 * jp + 1], h[q], b[2], b[3]);
                        }
                    }
                }
            }
#pragma unroll
            for (int r = 0; r < 2; r++) {
                uint4* row = r ? r1 : r0;
                uint32_t pv[8];
#pragma unroll
                for (int j = 0; j < 8; j++) pv[j] = pack_bf16(p[j][2 * r], p[j][2 * r + 1]);
#pragma unroll
                for (int c = 1; c < 4; c++) {
                    uint4 vx[2] = {row[c * 8], row[c * 8 + 1]};
                    const uint32_t* vv = reinterpret_cast<const uint32_t*>(vx);
                    uint32_t u[8];
#pragma unroll
                    for (int j = 0; j < 8; j++) u[j] = hmul2(pv[j], vv[j]);
                    row[c * 8] = make_uint4(__byte_perm(u[0], u[1], 0x5410), __byte_perm(u[2], u[3], 0x5410),
                                            __byte_perm(u[4], u[5], 0x5410), __byte_perm(u[6], u[7], 0x5410));
                    row[c * 8 + 1] = make_uint4(__byte_perm(u[0], u[1], 0x7632), __byte_perm(u[2], u[3], 0x7632),
                                                __byte_perm(u[4], u[5], 0x7632), __byte_perm(u[6], u[7], 0x7632));
                }
            }
            asm volatile("fence.proxy.async.shared::cta;" ::: "memory");
            __syncwarp();
            if (tid == 0) STAMP(3);
            if (lane == 0) {
                bulk_s2g(g_tab + (size_t)tile * 16 * ROWB, smem_u32(tb), nrows * 512);
                asm volatile("cp.async.bulk.commit_group;" ::: "memory");
                asm volatile("cp.async.bulk.wait_group 0;" ::: "memory");
            }
            if (tid == 0) STAMP(4);
        }
    } else {
        const int ptid = tid - 32 * P1_WARPS, pwarp = warp - P1_WARPS;
        const uint32_t bar = smem_u32(smem + PS_BAR);
        const int posbytes = N * 6;
        if (ptid == 0) {
            mbar_init(bar, 1);
            asm volatile("fence.mbarrier_init.release.cluster;" ::: "memory");
            mbar_expect_tx(bar, posbytes);
            bulk_g2s(smem_u32(smem + PS_POS), pos, posbytes, bar);
        }
        const int npairs = E >> 1;
        const int ppc = (npairs + NCTA - 1) / NCTA;
        const int pbeg = blockIdx.x * ppc, pend = min(pbeg + ppc, npairs);
        int2 es[P3_ITERS], ed[P3_ITERS];
#pragma unroll
        for (int it = 0; it < P3_ITERS; it++) {
            const int p = pbeg + ptid + it * P3_THREADS;
            if (p < pend) {
                es[it] = __ldcs(reinterpret_cast<const int2*>(src) + p);
                ed[it] = __ldcs(reinterpret_cast<const int2*>(dst) + p);
            }
        }
        int* hist = reinterpret_cast<int*>(smem + PS_HIST);
        for (int i = ptid; i < 1280; i += P3_THREADS) hist[i] = 0;
        {
            const int gi = ptid * NCTA + blockIdx.x;
            if (gi < NTAB * NRBF) {
                const int di = gi >> 4, k = gi & 15;
                const float d = __uint_as_float((uint32_t)(DBASE + di) << 16);
                const float arg = bf16r(d * __bfloat162float(freqs[k]));
                const float rbf = bf16r(bf16r(sinf(arg)) / d);
                const float ca = bf16r(bf16r(3.14159265358979f * d) / 5.0f);
                const float fc = 0.5f * bf16r(bf16r(cosf(ca)) + 1.0f);
                g_G[gi] = __float2bfloat16_rn(rbf * fc);
            }
        }
        if (ptid == 0) STAMP(5);
        asm volatile("bar.sync 2, %0;" ::"n"(P3_THREADS) : "memory");
        if (ptid == 0) STAMP(6);
        mbar_wait(bar, 0);
        if (ptid == 0) STAMP(7);
        const uint32_t* pw = reinterpret_cast<const uint32_t*>(smem + PS_POS);
        uint2 rec[P3_ITERS * 2];
        int key[P3_ITERS * 2];
#pragma unroll
        for (int q = 0; q < P3_ITERS * 2; q++) {
            const int it = q >> 1;
            key[q] = -1;
            if (pbeg + ptid + it * P3_THREADS < pend) {
                const int s = (q & 1) ? es[it].y : es[it].x;
                const int dd = (q & 1) ? ed[it].y : ed[it].x;
                const int ws = (s * 3) >> 1, wd = (dd * 3) >> 1;
                const uint32_t sa = pw[ws], sb = pw[ws + 1], da = pw[wd], db = pw[wd + 1];
                const uint32_t shs = (s & 1) << 4, shd = (dd & 1) << 4;
                const uint32_t rxy = hsub2(__funnelshift_r(sa, sb, shs), __funnelshift_r(da, db, shd));
                const uint32_t rz = hsub2(sb >> shs, db >> shd);
                const uint32_t qxy = hmul2(rxy, rxy), qz = hmul2(rz, rz);
                const float sum = (__uint_as_float(qxy << 16) + __uint_as_float(qxy & 0xffff0000u)) + __uint_as_float(qz << 16);
                if (sum < 23.9375f) {
                    const uint32_t exy = hmul2(rxy, 0x1e801e80u), ez = hmul2(rz, 0x1e801e80u);
                    rec[q].x = exy | ((dd & 3) << 13) | ((dd & 12) << 27);
                    rec[q].y = (ez & 0xffffu) | ((dd & 48) << 9) | ((uint32_t)s << 16) | ((uint32_t)(dd & 64) << 25);
                    const int grp = dd >> 3;
                    key[q] = (grp << 13) | atomicAdd(&hist[grp], 1);
                }
            }
        }
        if (ptid == 0) STAMP(8);
        asm volatile("bar.sync 2, %0;" ::"n"(P3_THREADS) : "memory");
        if (ptid == 0) STAMP(9);
        int2 hv = make_int2(0, 0);
        int incl = 0;
        if (pwarp < 20) {
            hv = reinterpret_cast<int2*>(hist)[ptid];
            incl = hv.x + hv.y;
#pragma unroll
            for (int o = 1; o < 32; o <<= 1) {
                const int v = __shfl_up_sync(0xffffffffu, incl, o);
                if (lane >= o) incl += v;
            }
            if (lane == 31) hist[1280 + pwarp] = incl;
        }
        asm volatile("bar.sync 2, %0;" ::"n"(P3_THREADS) : "memory");
        if (pwarp < 20) {
            int wsum = (lane < pwarp) ? hist[1280 + lane] : 0;
            wsum = __reduce_add_sync(0xffffffffu, wsum);
            const int ex = wsum + incl - hv.x - hv.y;
            reinterpret_cast<int2*>(hist)[ptid] = make_int2(ex, ex + hv.x);
        }
        asm volatile("bar.sync 2, %0;" ::"n"(P3_THREADS) : "memory");
        if (ptid == 0) STAMP(10);
        uint2* srec = reinterpret_cast<uint2*>(smem + PS_REC);
#pragma unroll
        for (int q = 0; q < P3_ITERS * 2; q++)
            if (key[q] >= 0) srec[hist[key[q] >> 13] + (key[q] & 8191)] = rec[q];
        const int ngroups = (N + GRP - 1) / GRP;
        unsigned short* spfx = reinterpret_cast<unsigned short*>(smem + PS_PFX);
        for (int i = ptid; i < NCTA * 16; i += P3_THREADS)
            spfx[i] = (unsigned short)hist[min(group_begin(i >> 4, ngroups) + (i & 15), ngroups)];
        asm volatile("fence.proxy.async.shared::cta;" ::: "memory");
        asm volatile("bar.sync 2, %0;" ::"n"(P3_THREADS) : "memory");
        if (ptid == 0) {
            STAMP(11);
            const int total = hist[ngroups];
            const int bytes = ((total + 1) >> 1) * 16;
            if (bytes > 0) bulk_s2g(g_rec + blockIdx.x * CH, smem_u32(srec), bytes);
            bulk_s2g(g_pfx + blockIdx.x * NCTA * 16, smem_u32(spfx), NCTA * 32);
            asm volatile("cp.async.bulk.commit_group;" ::: "memory");
            asm volatile("cp.async.bulk.wait_group 0;" ::: "memory");
            STAMP(12);
        }
    }
}

constexpr int UNITS = 3;
constexpr int STAGES = 3;
constexpr int M_THREADS = UNITS * 128 + 128;
constexpr int ST_G = 4 * 4096;
constexpr int ST_S = ST_G + 1024;
constexpr int STAGE_BYTES = ST_S + 2048;
constexpr int RCAP = 4736;
constexpr int MAXQ = 10;
constexpr int HOT0 = 0x3F00 - DBASE;
constexpr int MS_REC = UNITS * STAGES * STAGE_BYTES;
constexpr int MS_GH = MS_REC + RCAP * 8;
constexpr int MS_B2 = MS_GH + (NTAB - HOT0) * 32;
constexpr int MS_MISC = MS_B2 + MAXQ * 136 * 4;
constexpr int MS_BAR = MS_MISC + 32 * 4;
constexpr int M_SMEM = MS_BAR + (2 * UNITS * STAGES + 1) * 8;
static_assert(M_SMEM <= 232448, "smem");
static_assert(MS_BAR % 8 == 0 && MS_GH % 16 == 0 && STAGE_BYTES % 1024 == 0, "align");

template <int ACC, uint32_t HI>
__device__ __forceinline__ void wgmma_n32(float (&d)[16], const uint32_t (&a)[4], uint32_t lo) {
    if (ACC) {
        asm volatile("{\n.reg .b64 dd;\nmov.b64 dd, {%20, %21};\n"
                     "wgmma.mma_async.sync.aligned.m64n32k16.f32.bf16.bf16 {%0,%1,%2,%3,%4,%5,%6,%7,%8,%9,%10,%11,%12,%13,%14,%15}, {%16,%17,%18,%19}, dd, 1, 1, 1, 0;\n}\n"
                     : "+f"(d[0]), "+f"(d[1]), "+f"(d[2]), "+f"(d[3]), "+f"(d[4]), "+f"(d[5]), "+f"(d[6]), "+f"(d[7]),
                       "+f"(d[8]), "+f"(d[9]), "+f"(d[10]), "+f"(d[11]), "+f"(d[12]), "+f"(d[13]), "+f"(d[14]), "+f"(d[15])
                     : "r"(a[0]), "r"(a[1]), "r"(a[2]), "r"(a[3]), "r"(lo), "n"(HI));
    } else {
        asm volatile("{\n.reg .b64 dd;\nmov.b64 dd, {%20, %21};\n"
                     "wgmma.mma_async.sync.aligned.m64n32k16.f32.bf16.bf16 {%0,%1,%2,%3,%4,%5,%6,%7,%8,%9,%10,%11,%12,%13,%14,%15}, {%16,%17,%18,%19}, dd, 0, 1, 1, 0;\n}\n"
                     : "=f"(d[0]), "=f"(d[1]), "=f"(d[2]), "=f"(d[3]), "=f"(d[4]), "=f"(d[5]), "=f"(d[6]), "=f"(d[7]),
                       "=f"(d[8]), "=f"(d[9]), "=f"(d[10]), "=f"(d[11]), "=f"(d[12]), "=f"(d[13]), "=f"(d[14]), "=f"(d[15])
                     : "r"(a[0]), "r"(a[1]), "r"(a[2]), "r"(a[3]), "r"(lo), "n"(HI));
    }
}
constexpr uint32_t DESC_H = 64u | (1u << 30);
constexpr uint32_t DESC_G = 16u | (3u << 30);
__device__ __forceinline__ void reg_fence16(float (&d)[16]) {
    asm volatile("" : "+f"(d[0]), "+f"(d[1]), "+f"(d[2]), "+f"(d[3]), "+f"(d[4]), "+f"(d[5]), "+f"(d[6]), "+f"(d[7]),
                      "+f"(d[8]), "+f"(d[9]), "+f"(d[10]), "+f"(d[11]), "+f"(d[12]), "+f"(d[13]), "+f"(d[14]), "+f"(d[15]) :: "memory");
}
__device__ __forceinline__ uint32_t opaque(uint32_t x) { asm volatile("" : "+r"(x)); return x; }

__global__ void __launch_bounds__(M_THREADS, 1)
main_kernel(const __nv_bfloat16* __restrict__ sv, const __nv_bfloat16* __restrict__ w2,
            const __nv_bfloat16* __restrict__ wrbf, __nv_bfloat16* __restrict__ out, int N) {
    extern __shared__ __align__(1024) unsigned char smem[];
    const int tid = threadIdx.x, warp = tid >> 5, lane = tid & 31;
    const int g = lane >> 2, t = lane & 3;
    const int ngroups = (N + GRP - 1) / GRP;
    const int q0 = group_begin(blockIdx.x, ngroups);
    const int nq = group_begin(blockIdx.x + 1, ngroups) - q0;
    const uint32_t sbase = smem_u32(smem);
    const uint32_t ghbar = sbase + MS_BAR + 2 * UNITS * STAGES * 8;
    int* misc = reinterpret_cast<int*>(smem + MS_MISC);
    const bool is_prod = warp >= UNITS * 4;

    if (tid == 0) {
        STAMP(16);
        for (int i = 0; i < UNITS * STAGES; i++) {
            mbar_init(sbase + MS_BAR + i * 16, 33);
            mbar_init(sbase + MS_BAR + i * 16 + 8, 4);
        }
        mbar_init(ghbar, 1);
        asm volatile("fence.mbarrier_init.release.cluster;" ::: "memory");
        misc[16] = UNITS;
    }
    if (tid == 0) STAMP(17);
    asm volatile("griddepcontrol.wait;" ::: "memory");
    if (tid == 0) STAMP(18);

    const unsigned short* pfx = g_pfx + blockIdx.x * 16;
    int* b2 = reinterpret_cast<int*>(smem + MS_B2);
    uint2* srec = reinterpret_cast<uint2*>(smem + MS_REC);
    {
        if (tid == 0) {
            mbar_expect_tx(ghbar, (NTAB - HOT0) * 32);
            bulk_g2s(sbase + MS_GH, g_G + HOT0 * NRBF, (NTAB - HOT0) * 32, ghbar);
        }
        int beg = 0, end = 0;
        {
            const int p = warp + 16 * lane;
            if (p < NCTA) {
                beg = __ldcg(pfx + p * NCTA * 16);
                end = __ldcg(pfx + p * NCTA * 16 + nq);
            }
        }
        int lo[5], cq[5];
        if (warp < nq) {
#pragma unroll
            for (int k = 0; k < 5; k++) {
                const int p = lane * 5 + k;
                lo[k] = 0; cq[k] = 0;
                if (p < NCTA) {
                    lo[k] = __ldcg(pfx + p * NCTA * 16 + warp);
                    cq[k] = __ldcg(pfx + p * NCTA * 16 + warp + 1);
                }
            }
        }
        uint2 r[9];
#pragma unroll
        for (int k = 0; k < 9; k++) {
            const int i = __shfl_sync(0xffffffffu, beg, k) + lane;
            const int e = __shfl_sync(0xffffffffu, end, k);
            if (i < e) r[k] = __ldcg(g_rec + (warp + 16 * k) * CH + i);
        }
        int pre = 0;
        if (warp < nq) {
            int sum = 0;
#pragma unroll
            for (int k = 0; k < 5; k++) { cq[k] -= lo[k]; sum += cq[k]; }
            int in2 = sum;
#pragma unroll
            for (int o = 1; o < 32; o <<= 1) {
                const int v = __shfl_up_sync(0xffffffffu, in2, o);
                if (lane >= o) in2 += v;
            }
            pre = in2 - sum;
            if (lane == 31) misc[warp] = in2;
        }
        __syncthreads();
        if (tid == 0) STAMP(19);
        const int tv = lane < nq ? misc[lane] : 0;
        const bool fits = __reduce_add_sync(0xffffffffu, tv) <= RCAP;
        if (warp < nq) {
            if (fits) pre += __reduce_add_sync(0xffffffffu, lane < warp ? tv : 0);
#pragma unroll
            for (int k = 0; k < 5; k++) {
                const int p = lane * 5 + k;
                if (p < NCTA) b2[warp * 136 + p] = fits ? pre - lo[k] : pre;
                pre += cq[k];
            }
        }
        __syncthreads();
        if (fits) {
#pragma unroll
            for (int k = 0; k < 9; k++) {
                const int p = warp + 16 * k;
                int i = __shfl_sync(0xffffffffu, beg, k) + lane;
                const int e = __shfl_sync(0xffffffffu, end, k);
                uint2 v = r[k];
                while (i < e) {
                    const int q = (int)((((v.x >> 30) & 1u) | ((v.y >> 12) & 6u) | ((v.y >> 28) & 8u)) - (uint32_t)q0) & 15;
                    srec[b2[q * 136 + p] + i] = v;
                    i += 32;
                    if (i < e) v = __ldcg(g_rec + p * CH + i);
                }
            }
        }
        if (tid == 0) misc[17] = fits;
        __syncthreads();
    }
    if (tid == 0) STAMP(20);

    if (is_prod) {
        asm volatile("setmaxnreg.dec.sync.aligned.u32 56;");
        const int unit = warp - UNITS * 4;
        const uint32_t ubase = sbase + unit * STAGES * STAGE_BYTES;
        const uint32_t ubar = sbase + MS_BAR + unit * STAGES * 16;
        const uint32_t uflag = sbase + MS_MISC + (20 + unit * STAGES) * 4;
        if (unit < UNITS) {
            const bool fits = misc[17] != 0;
            mbar_wait(ghbar, 0);
            if (unit == 0 && lane == 0) STAMP(21);
            const int ln = opaque(lane);
            const unsigned char* gsrc = g_tab + (ln & 7) * 16;
            asm volatile("" : "+l"(gsrc));
            const int r4 = opaque(ln >> 3);
            const uint32_t d0 = opaque(r4 * 128 + (((ln & 7) ^ r4) << 4));
            const uint32_t zoff = opaque(ST_S + ln * 16);
            const uint32_t goff = opaque(ST_G + ln * 32 + (((ln >> 2) & 1) << 4));
            uint32_t sb = ubase, bar = ubar, flg = uflag, ph = 1;
            int q = unit;
            while (q < nq) {
                int base = (ln < q) ? misc[ln] : 0;
                base = __reduce_add_sync(0xffffffffu, base) + ln;
                const int cnt = misc[q];
                int rem = cnt;
                const int grp = q0 + q;
                bool last;
                do {
                    const bool valid = ln < rem;
                    last = rem <= 24;
                    uint2 r = make_uint2(0, 0);
                    if (fits) {
                        if (valid) r = srec[base];
                    } else if (valid) {
                        const int j = cnt - rem + ln;
                        const int* prq = b2 + q * 136;
                        int lo = 0, hi = NCTA;
                        while (hi - lo > 1) {
                            const int mid = (lo + hi) >> 1;
                            if (prq[mid] <= j) lo = mid; else hi = mid;
                        }
                        r = __ldcg(g_rec + lo * CH + __ldcg(pfx + lo * NCTA * 16 + q) + (j - prq[lo]));
                    }
                    base += 32;
                    const uint32_t srcv = (r.y >> 16) & 0x7fffu;
                    const unsigned char* gq[8];
#pragma unroll
                    for (int k = 0; k < 8; k++)
                        gq[k] = gsrc + (size_t)__shfl_sync(0xffffffffu, srcv, k * 4 + r4) * ROWB;
                    int lim6 = rem - 24;
                    if (last) {
                        const int node = grp * GRP + r4;
                        gq[6] = reinterpret_cast<const unsigned char*>(sv) + (size_t)node * 512 + (ln & 7) * 16;
                        gq[7] = gq[6] + 4 * 512;
                        lim6 = N - grp * GRP;
                    }
                    mbar_wait(bar + 8, ph);
                    const uint32_t dpa = sb + d0, dpb = (dpa ^ 64u) + 512u;
#pragma unroll
                    for (int k = 0; k < 8; k++) {
                        asm volatile("{\n.reg .pred p;\nsetp.ge.s32 p, %2, %3;\n"
                                     "cp.async.cg.shared.global [%0], [%1], 16, p;\n"
                                     "cp.async.cg.shared.global [%0+4096], [%1+128], 16, p;\n"
                                     "cp.async.cg.shared.global [%0+8192], [%1+256], 16, p;\n"
                                     "cp.async.cg.shared.global [%0+12288], [%1+384], 16, p;\n}\n"
                                     ::"r"(((k & 1) ? dpb : dpa) + (k >> 1) * 1024), "l"(gq[k]), "r"(r4),
                                       "r"(k < 6 ? rem - 4 * k : lim6 - 4 * (k - 6)) : "memory");
                    }
                    asm volatile("cp.async.mbarrier.arrive.noinc.shared::cta.b64 [%0];" ::"r"(bar) : "memory");
#pragma unroll
                    for (int j = 0; j < 4; j++)
                        asm volatile("st.shared.v4.u32 [%0], {%1,%1,%1,%1};" ::"r"(sb + zoff + j * 512), "r"(0u) : "memory");
                    const uint32_t rxy = hmul2(r.x & 0x9fff9fffu, 0x60806080u);
                    const uint32_t rz2 = hmul2(r.y & 0x00009fffu, 0x60806080u);
                    const uint32_t qxy = hmul2(rxy, rxy), qz = hmul2(rz2, rz2);
                    const float sum = bf16r((__uint_as_float(qxy << 16) + __uint_as_float(qxy & 0xffff0000u)) + __uint_as_float(qz << 16));
                    float sq;
                    asm("sqrt.approx.ftz.f32 %0, %1;" : "=f"(sq) : "f"(bf16r(sum + 1e-8f)));
                    const uint32_t dbits = pack_bf16(0.f, sq);
                    float rinv;
                    asm("rcp.approx.ftz.f32 %0, %1;" : "=f"(rinv) : "f"(__uint_as_float(dbits)));
                    const int di = min((int)(dbits >> 16), DEND - 1) - DBASE;
                    uint4 g0 = make_uint4(0, 0, 0, 0), g1 = g0;
                    if (di >= HOT0) {
                        const uint32_t ga = sbase + MS_GH - HOT0 * 32 + di * 32;
                        asm volatile("ld.shared.v4.u32 {%0,%1,%2,%3}, [%4];" : "=r"(g0.x), "=r"(g0.y), "=r"(g0.z), "=r"(g0.w) : "r"(ga));
                        asm volatile("ld.shared.v4.u32 {%0,%1,%2,%3}, [%4+16];" : "=r"(g1.x), "=r"(g1.y), "=r"(g1.z), "=r"(g1.w) : "r"(ga));
                    } else if (valid) {
                        const uint4* gp = reinterpret_cast<const uint4*>(g_G) + 2 * max(di, 0);
                        g0 = __ldcg(gp); g1 = __ldcg(gp + 1);
                    }
                    const uint32_t r01 = pack_bf16(__uint_as_float(rxy << 16) * rinv, __uint_as_float(rxy & 0xffff0000u) * rinv);
                    const uint32_t r2 = pack_bf16(__uint_as_float(rz2 << 16) * rinv, valid ? 1.0f : 0.f);
                    const uint32_t sa = sb + zoff + (((r.x >> 12) & 6u) | ((r.x >> 26) & 8u));
                    asm volatile("st.shared.u16 [%0], %1;" ::"r"(sa), "h"((unsigned short)(r2 >> 16)) : "memory");
                    asm volatile("st.shared.u16 [%0+512], %1;" ::"r"(sa), "h"((unsigned short)(r01 & 0xffffu)) : "memory");
                    asm volatile("st.shared.u16 [%0+1024], %1;" ::"r"(sa), "h"((unsigned short)(r01 >> 16)) : "memory");
                    asm volatile("st.shared.u16 [%0+1536], %1;" ::"r"(sa), "h"((unsigned short)(r2 & 0xffffu)) : "memory");
                    asm volatile("st.shared.u32 [%0], %1;" ::"r"(flg),
                                 "r"(((uint32_t)grp << 4) | (last ? 2u : 0u) | (rem > 0 ? 1u : 0u)) : "memory");
                    asm volatile("st.shared.v4.u32 [%0], {%1,%2,%3,%4};" ::"r"(sb + goff),
                                 "r"(g0.x), "r"(g0.y), "r"(g0.z), "r"(g0.w) : "memory");
                    asm volatile("st.shared.v4.u32 [%0], {%1,%2,%3,%4};" ::"r"((sb + goff) ^ 16u),
                                 "r"(g1.x), "r"(g1.y), "r"(g1.z), "r"(g1.w) : "memory");
                    __syncwarp();
                    if (ln == 0) mbar_arrive(bar);
                    sb += STAGE_BYTES; bar += 16; flg += 4;
                    if (sb == ubase + STAGES * STAGE_BYTES) { sb = ubase; bar = ubar; flg = uflag; ph ^= 1; }
                    rem -= 32;
                } while (!last);
                int nx = 0;
                if (ln == 0) nx = atomicAdd(&misc[16], 1);
                q = __shfl_sync(0xffffffffu, nx, 0);
            }
            mbar_wait(bar + 8, ph);
            asm volatile("st.shared.u32 [%0], %1;" ::"r"(flg), "r"(8u) : "memory");
            __syncwarp();
            mbar_arrive(bar);
            if (ln == 0) mbar_arrive(bar);
            if (ln == 0) STAMP(22 + unit);
        }
    } else {
        asm volatile("setmaxnreg.inc.sync.aligned.u32 152;");
        const int unit = warp >> 2, w = warp & 3;
        const uint32_t ubase = sbase + unit * STAGES * STAGE_BYTES;
        const uint32_t ubar = sbase + MS_BAR + unit * STAGES * 16;
        const uint32_t uflag = sbase + MS_MISC + (20 + unit * STAGES) * 4;
        uint32_t wa[3][4], pa[2][4][4];
        {
            const int c = 16 * w + 2 * g;
#pragma unroll
            for (int p = 0; p < 3; p++)
#pragma unroll
                for (int kh = 0; kh < 2; kh++) {
                    const uint32_t lo = __ldg(reinterpret_cast<const uint32_t*>(wrbf + (2 * t + 8 * kh) * 192 + p * 64 + c));
                    const uint32_t hi = __ldg(reinterpret_cast<const uint32_t*>(wrbf + (2 * t + 8 * kh + 1) * 192 + p * 64 + c));
                    wa[p][2 * kh + 0] = __byte_perm(lo, hi, 0x5410);
                    wa[p][2 * kh + 1] = __byte_perm(lo, hi, 0x7632);
                }
#pragma unroll
            for (int p = 0; p < 2; p++)
#pragma unroll
                for (int q = 0; q < 4; q++)
#pragma unroll
                    for (int kh = 0; kh < 2; kh++) {
                        const int r = 8 * (t + 4 * kh) + 2 * q;
                        const uint32_t lo = __ldg(reinterpret_cast<const uint32_t*>(w2 + r * 192 + p * 128 + c));
                        const uint32_t hi = __ldg(reinterpret_cast<const uint32_t*>(w2 + (r + 1) * 192 + p * 128 + c));
                        pa[p][q][2 * kh + 0] = __byte_perm(lo, hi, 0x5410);
                        pa[p][q][2 * kh + 1] = __byte_perm(lo, hi, 0x7632);
                    }
        }
        float acc[4][4];
#pragma unroll
        for (int c = 0; c < 4; c++)
#pragma unroll
            for (int e = 0; e < 4; e++) acc[c][e] = 0.f;
        const int erow = (lane & 7) + 8 * (lane >> 4);
        const int ehalf = (lane >> 3) & 1;
        const uint32_t ua = opaque(4096 + erow * 128 + ((uint32_t)((2 * w + ehalf) ^ (lane & 7)) << 4));
        const uint32_t sa = opaque(ST_S + lane * 16);
        const uint32_t ub = __shfl_sync(0xffffffffu, ubase, 0);
        uint32_t sb = ub, bar = ubar, flg = uflag;
        uint32_t ph = 0;
        const bool elected = opaque(lane) == 0;
        while (true) {
            mbar_wait(bar, ph);
            uint32_t flags;
            asm volatile("ld.shared.u32 %0, [%1];" : "=r"(flags) : "r"(flg));
            if (flags & 1u) {
                asm volatile("fence.proxy.async.shared::cta;" ::: "memory");
                const uint32_t dh = (sb >> 4) | (1u << 16);
                const uint32_t dg = dh + (ST_G >> 4);
                uint32_t m[2][4], u[3][2][4], sf[4];
                {
                    float ps[16], fs[16], fv[16];
                    asm volatile("wgmma.fence.sync.aligned;" ::: "memory");
                    wgmma_n32<0, DESC_G>(fv, wa[1], dg);
                    wgmma_n32<0, DESC_G>(fs, wa[0], dg);
                    wgmma_n32<0, DESC_H>(ps, pa[0][0], dh);
                    wgmma_n32<1, DESC_H>(ps, pa[0][1], dh + 2);
                    wgmma_n32<1, DESC_H>(ps, pa[0][2], dh + 4);
                    wgmma_n32<1, DESC_H>(ps, pa[0][3], dh + 6);
                    asm volatile("wgmma.commit_group.sync.aligned;" ::: "memory");
#pragma unroll
                    for (int j = 0; j < 3; j++) {
                        ldsm4t(u[j][0], sb + ua + j * 4096);
                        ldsm4t(u[j][1], sb + ua + j * 4096 + 2048);
                    }
                    ldsm4t(sf, sb + sa);
                    asm volatile("wgmma.wait_group.sync.aligned 0;" ::: "memory");
                    reg_fence16(fv); reg_fence16(fs); reg_fence16(ps);
#pragma unroll
                    for (int i = 0; i < 8; i++)
                        m[i >> 2][i & 3] = opaque(pack_bf16(fs[2 * i] * ps[2 * i], fs[2 * i + 1] * ps[2 * i + 1]));
                    float pr[16], fr[16];
                    asm volatile("wgmma.fence.sync.aligned;" ::: "memory");
                    wgmma_n32<0, DESC_G>(fr, wa[2], dg);
                    wgmma_n32<0, DESC_H>(pr, pa[1][0], dh);
                    wgmma_n32<1, DESC_H>(pr, pa[1][1], dh + 2);
                    wgmma_n32<1, DESC_H>(pr, pa[1][2], dh + 4);
                    wgmma_n32<1, DESC_H>(pr, pa[1][3], dh + 6);
                    asm volatile("wgmma.commit_group.sync.aligned;" ::: "memory");
#pragma unroll
                    for (int i = 0; i < 8; i++) {
                        const uint32_t wv = pack_bf16(fv[2 * i], fv[2 * i + 1]);
#pragma unroll
                        for (int j = 0; j < 3; j++) u[j][i >> 2][i & 3] = opaque(hmul2(u[j][i >> 2][i & 3], wv));
                    }
                    uint32_t sj[3][4];
#pragma unroll
                    for (int j = 0; j < 3; j++) ldsm4t(sj[j], sb + sa + (j + 1) * 512);
#pragma unroll
                    for (int s = 0; s < 2; s++) {
                        mma16816(acc[0], m[s], sf[2 * s], sf[2 * s + 1]);
#pragma unroll
                        for (int j = 0; j < 3; j++) mma16816(acc[j + 1], u[j][s], sf[2 * s], sf[2 * s + 1]);
                    }
                    asm volatile("wgmma.wait_group.sync.aligned 0;" ::: "memory");
                    reg_fence16(fr); reg_fence16(pr);
#pragma unroll
                    for (int i = 0; i < 8; i++)
                        m[i >> 2][i & 3] = pack_bf16(fr[2 * i] * pr[2 * i], fr[2 * i + 1] * pr[2 * i + 1]);
#pragma unroll
                    for (int s = 0; s < 2; s++)
#pragma unroll
                        for (int j = 0; j < 3; j++) mma16816(acc[j + 1], m[s], sj[j][2 * s], sj[j][2 * s + 1]);
                }
            } else if (flags & 8u) {
                break;
            }
            if (flags & 2u) {
                const int node0 = (int)(flags >> 4) * GRP + 2 * t;
                uint32_t* op = reinterpret_cast<uint32_t*>(out) + (size_t)node0 * 128 + 8 * w + g;
#pragma unroll
                for (int b = 0; b < 2; b++) {
                    const uint32_t va = sb + (24 + 2 * t + b) * 128 + (((uint32_t)(2 * w + (g >> 2)) ^ (uint32_t)(2 * t + b)) << 4) + (g & 3) * 4;
#pragma unroll
                    for (int c = 0; c < 4; c++) {
                        uint32_t v;
                        asm volatile("ld.shared.u32 %0, [%1];" : "=r"(v) : "r"(va + c * 4096));
                        const uint32_t o = pack_bf16(__uint_as_float(v << 16) + acc[c][b],
                                                     __uint_as_float(v & 0xffff0000u) + acc[c][2 + b]);
                        if (node0 + b < N) op[b * 128 + c * 32] = o;
                        acc[c][b] = 0.f; acc[c][2 + b] = 0.f;
                    }
                }
            }
            __syncwarp();
            if (elected) mbar_arrive(bar + 8);
            sb += STAGE_BYTES; bar += 16; flg += 4;
            if (sb == ub + STAGES * STAGE_BYTES) { sb = ub; bar -= STAGES * 16; flg -= STAGES * 4; ph ^= 1; }
        }
        if (lane == 0 && w == 0) STAMP(26 + unit);
    }
}

}

extern "C" void kernel_launch(void* const* d_in, const int* in_sizes, int n_in, void* d_out, int out_size) {
    const __nv_bfloat16* sv = (const __nv_bfloat16*)d_in[0];
    const __nv_bfloat16* pos = (const __nv_bfloat16*)d_in[1];
    const int* src = (const int*)d_in[2];
    const int* dst = (const int*)d_in[3];
    const __nv_bfloat16* freqs = (const __nv_bfloat16*)d_in[4];
    const __nv_bfloat16* w1 = (const __nv_bfloat16*)d_in[5];
    const __nv_bfloat16* w2 = (const __nv_bfloat16*)d_in[6];
    const __nv_bfloat16* wrbf = (const __nv_bfloat16*)d_in[7];
    __nv_bfloat16* out = (__nv_bfloat16*)d_out;
    const int N = in_sizes[1] / 3;
    const int E = in_sizes[2];

    static bool init = false;
    if (!init) {
        cudaFuncSetAttribute(prep_kernel, cudaFuncAttributeMaxDynamicSharedMemorySize, PS_TOTAL);
        cudaFuncSetAttribute(main_kernel, cudaFuncAttributeMaxDynamicSharedMemorySize, M_SMEM);
        init = true;
    }
    cudaStream_t stream = cudaStreamPerThread;
    prep_kernel<<<NCTA, P_THREADS, PS_TOTAL, stream>>>(sv, pos, src, dst, freqs, w1, w2, N, E);

    cudaLaunchConfig_t cfg = {};
    cfg.gridDim = dim3(NCTA);
    cfg.blockDim = dim3(M_THREADS);
    cfg.dynamicSmemBytes = M_SMEM;
    cfg.stream = stream;
    cudaLaunchAttribute at[1];
    at[0].id = cudaLaunchAttributeProgrammaticStreamSerialization;
    at[0].val.programmaticStreamSerializationAllowed = 1;
    cfg.attrs = at;
    cfg.numAttrs = 1;
    cudaLaunchKernelEx(&cfg, main_kernel, sv, w2, wrbf, out, N);
}
```

```cpp
#include <cuda_runtime.h>
#include <cuda_bf16.h>
#include <stdint.h>

namespace {

constexpr int D = 64;
constexpr int NRBF = 16;
constexpr int MAXN = 10000;
constexpr int MAXE = 640000;
constexpr int NCTA = 132;
constexpr int GRP = 8;
constexpr int MAXG = (MAXN + GRP - 1) / GRP;
constexpr int CH = 4864;
constexpr int DBASE = 0x38C0;
constexpr int DEND = 0x40A0;
constexpr int NTAB = DEND - DBASE;
constexpr int ROWB = 512;

__device__ __align__(128) unsigned char g_tab[(size_t)(MAXN + 16) * ROWB];
__device__ __align__(128) __nv_bfloat16 g_G[NTAB * NRBF];
__device__ __align__(128) uint2 g_rec[NCTA * CH];
__device__ __align__(128) unsigned short g_pfx[NCTA * NCTA * 16];

#define STAMP(k) do {} while (0)

__device__ __forceinline__ uint32_t smem_u32(const void* p) { return (uint32_t)__cvta_generic_to_shared(p); }
__device__ __forceinline__ uint32_t pack_bf16(float lo, float hi) {
    uint32_t r;
    asm("cvt.rn.bf16x2.f32 %0, %1, %2;" : "=r"(r) : "f"(hi), "f"(lo));
    return r;
}
__device__ __forceinline__ float bf16r(float x) { return __uint_as_float(pack_bf16(0.f, x) & 0xffff0000u); }
__device__ __forceinline__ uint32_t hmul2(uint32_t a, uint32_t b) {
    uint32_t r;
    asm("mul.rn.bf16x2 %0, %1, %2;" : "=r"(r) : "r"(a), "r"(b));
    return r;
}
__device__ __forceinline__ uint32_t hsub2(uint32_t a, uint32_t b) {
    uint32_t r;
    asm("sub.rn.bf16x2 %0, %1, %2;" : "=r"(r) : "r"(a), "r"(b));
    return r;
}
__device__ __forceinline__ uint32_t hfma2(uint32_t a, uint32_t b, uint32_t c) {
    uint32_t r;
    asm("fma.rn.bf16x2 %0, %1, %2, %3;" : "=r"(r) : "r"(a), "r"(b), "r"(c));
    return r;
}
__device__ __forceinline__ void mma16816(float (&c)[4], const uint32_t (&a)[4], uint32_t b0, uint32_t b1) {
    asm volatile("mma.sync.aligned.m16n8k16.row.col.f32.bf16.bf16.f32 {%0,%1,%2,%3}, {%4,%5,%6,%7}, {%8,%9}, {%0,%1,%2,%3};"
                 : "+f"(c[0]), "+f"(c[1]), "+f"(c[2]), "+f"(c[3])
                 : "r"(a[0]), "r"(a[1]), "r"(a[2]), "r"(a[3]), "r"(b0), "r"(b1));
}
__device__ __forceinline__ void mma16816_z(float (&c)[4], const uint32_t (&a)[4], uint32_t b0, uint32_t b1) {
    asm volatile("mma.sync.aligned.m16n8k16.row.col.f32.bf16.bf16.f32 {%0,%1,%2,%3}, {%4,%5,%6,%7}, {%8,%9}, {%10,%10,%10,%10};"
                 : "=f"(c[0]), "=f"(c[1]), "=f"(c[2]), "=f"(c[3])
                 : "r"(a[0]), "r"(a[1]), "r"(a[2]), "r"(a[3]), "r"(b0), "r"(b1), "f"(0.f));
}
__device__ __forceinline__ void ldsm4(uint32_t (&r)[4], uint32_t addr) {
    asm volatile("ldmatrix.sync.aligned.m8n8.x4.shared.b16 {%0,%1,%2,%3}, [%4];"
                 : "=r"(r[0]), "=r"(r[1]), "=r"(r[2]), "=r"(r[3]) : "r"(addr));
}
__device__ __forceinline__ void ldsm4t(uint32_t (&r)[4], uint32_t addr) {
    asm volatile("ldmatrix.sync.aligned.m8n8.x4.trans.shared.b16 {%0,%1,%2,%3}, [%4];"
                 : "=r"(r[0]), "=r"(r[1]), "=r"(r[2]), "=r"(r[3]) : "r"(addr));
}
__device__ __forceinline__ void mbar_init(uint32_t bar, int cnt) {
    asm volatile("mbarrier.init.shared::cta.b64 [%0], %1;" ::"r"(bar), "r"(cnt) : "memory");
}
__device__ __forceinline__ void mbar_arrive(uint32_t bar) {
    asm volatile("mbarrier.arrive.shared::cta.b64 _, [%0];" ::"r"(bar) : "memory");
}
__device__ __forceinline__ void mbar_expect_tx(uint32_t bar, uint32_t bytes) {
    asm volatile("mbarrier.arrive.expect_tx.shared::cta.b64 _, [%0], %1;" ::"r"(bar), "r"(bytes) : "memory");
}
__device__ __forceinline__ void mbar_wait(uint32_t bar, uint32_t parity) {
    asm volatile(
        "{\n.reg .pred p;\n.reg .u32 n;\nmov.u32 n, 0;\n"
        "WAIT_%=:\n"
        "mbarrier.try_wait.parity.shared::cta.b64 p, [%0], %1, %2;\n"
        "@p bra DONE_%=;\n"
        "add.u32 n, n, 1;\n"
        "setp.lt.u32 p, n, 100000;\n"
        "@p bra WAIT_%=;\n"
        "exit;\n"
        "DONE_%=:\n}\n" ::"r"(bar), "r"(parity), "r"(10000u) : "memory");
}
__device__ __forceinline__ void bulk_g2s(uint32_t dst, const void* src, uint32_t bytes, uint32_t bar) {
    asm volatile("cp.async.bulk.shared::cluster.global.mbarrier::complete_tx::bytes [%0], [%1], %2, [%3];"
                 ::"r"(dst), "l"(src), "r"(bytes), "r"(bar) : "memory");
}
__device__ __forceinline__ void bulk_s2g(void* dst, uint32_t src, uint32_t bytes) {
    asm volatile("cp.async.bulk.global.shared::cta.bulk_group [%0], [%1], %2;" ::"l"(dst), "r"(src), "r"(bytes) : "memory");
}
__device__ __forceinline__ int group_begin(int c, int ngroups) { return (c * ngroups) / NCTA; }

constexpr int P_THREADS = 1024;
constexpr int P1_WARPS = 5;
constexpr int P3_THREADS = P_THREADS - 32 * P1_WARPS;
constexpr int P3_ITERS = 3;
constexpr int W_PITCH = 144;
constexpr int PS_TILE = 0;
constexpr int PS_REC = PS_TILE + P1_WARPS * 8192;
constexpr int PS_PFX = PS_REC + CH * 8;
constexpr int PS_POS = PS_PFX + NCTA * 32;
constexpr int PS_W1 = PS_POS + 60032;
constexpr int PS_W2 = PS_W1 + 64 * W_PITCH;
constexpr int PS_HIST = PS_W2 + 64 * W_PITCH;
constexpr int PS_BAR = PS_HIST + (1280 + 32) * 4;
constexpr int PS_TOTAL = PS_BAR + 64;

__global__ void __launch_bounds__(P_THREADS, 1)
prep_kernel(const __nv_bfloat16* __restrict__ sv, const __nv_bfloat16* __restrict__ pos,
            const int* __restrict__ src, const int* __restrict__ dst,
            const __nv_bfloat16* __restrict__ freqs, const __nv_bfloat16* __restrict__ w1,
            const __nv_bfloat16* __restrict__ w2, int N, int E) {
    extern __shared__ __align__(1024) unsigned char smem[];
    const int tid = threadIdx.x, warp = tid >> 5, lane = tid & 31;
    asm volatile("griddepcontrol.launch_dependents;");
    if (tid == 0) STAMP(0);

    if (warp < P1_WARPS) {
        const int g = lane >> 2, t = lane & 3;
        const int tile = warp * gridDim.x + blockIdx.x;
        const int nrows = min(16, N - tile * 16);
        const uint32_t bar = smem_u32(smem + PS_BAR + 8 + 8 * warp);
        unsigned char* tb = smem + PS_TILE + warp * 8192;
        if (nrows > 0 && lane == 0) {
            mbar_init(bar, 1);
            asm volatile("fence.mbarrier_init.release.cluster;" ::: "memory");
            mbar_expect_tx(bar, nrows * 512);
            bulk_g2s(smem_u32(tb), sv + (size_t)tile * 16 * 256, nrows * 512, bar);
        }
        for (int i = tid; i < 64 * 8; i += 32 * P1_WARPS) {
            const int r = i >> 3, c = i & 7;
            *reinterpret_cast<uint4*>(smem + PS_W1 + r * W_PITCH + c * 16) =
                __ldg(reinterpret_cast<const uint4*>(w1 + r * 64) + c);
            const uint4 v = __ldg(reinterpret_cast<const uint4*>(w2 + r * 192 + 64) + c);
            const int tt = c >> 1, j0 = (c & 1) * 4;
            uint32_t* o = reinterpret_cast<uint32_t*>(smem + PS_W2 + r * W_PITCH);
            o[4 * (j0 + 0) + tt] = v.x; o[4 * (j0 + 1) + tt] = v.y;
            o[4 * (j0 + 2) + tt] = v.z; o[4 * (j0 + 3) + tt] = v.w;
        }
        asm volatile("bar.sync 1, %0;" ::"n"(32 * P1_WARPS) : "memory");
        if (tid == 0) STAMP(1);
        if (nrows > 0) {
            mbar_wait(bar, 0);
            if (tid == 0) STAMP(2);
            uint4* r0 = reinterpret_cast<uint4*>(tb + g * 512 + t * 32);
            uint4* r1 = reinterpret_cast<uint4*>(tb + (g + 8) * 512 + t * 32);
            uint32_t h[4][4];
            {
                uint4 xa[2] = {r0[0], r0[1]}, xb[2] = {r1[0], r1[1]};
                const uint32_t* s0 = reinterpret_cast<const uint32_t*>(xa);
                const uint32_t* s1 = reinterpret_cast<const uint32_t*>(xb);
                float a[8][4];
                const int i = lane & 7, hi = (lane >> 3) & 1, nsel = lane >> 4;
#pragma unroll
                for (int q = 0; q < 4; q++) {
                    const int krow = 16 * (i >> 1) + 4 * q + (i & 1) + 2 * hi;
                    const uint32_t af[4] = {s0[2 * q], s1[2 * q], s0[2 * q + 1], s1[2 * q + 1]};
#pragma unroll
                    for (int jp = 0; jp < 4; jp++) {
                        uint32_t b[4];
                        ldsm4t(b, smem_u32(smem + PS_W1 + krow * W_PITCH + (2 * jp + nsel) * 16));
                        if (q == 0) {
                            mma16816_z(a[2 * jp], af, b[0], b[1]);
                            mma16816_z(a[2 * jp + 1], af, b[2], b[3]);
                        } else {
                            mma16816(a[2 * jp], af, b[0], b[1]);
                            mma16816(a[2 * jp + 1], af, b[2], b[3]);
                        }
                    }
                }
#pragma unroll
                for (int j = 0; j < 8; j++) {
                    float f[4];
#pragma unroll
                    for (int e = 0; e < 4; e++) {
                        const float z = bf16r(a[j][e]);
                        f[e] = __fdividef(z, 1.0f + __expf(-z));
                    }
                    h[j >> 1][(j & 1) * 2 + 0] = pack_bf16(f[0], f[1]);
                    h[j >> 1][(j & 1) * 2 + 1] = pack_bf16(f[2], f[3]);
                }
            }
            r0[0] = make_uint4(h[0][0], h[0][2], h[1][0], h[1][2]);
            r0[1] = make_uint4(h[2][0], h[2][2], h[3][0], h[3][2]);
            r1[0] = make_uint4(h[0][1], h[0][3], h[1][1], h[1][3]);
            r1[1] = make_uint4(h[2][1], h[2][3], h[3][1], h[3][3]);
            float p[8][4];
            {
                const int i = lane & 15, nsel = lane >> 4;
#pragma unroll
                for (int q = 0; q < 4; q++) {
#pragma unroll
                    for (int jp = 0; jp < 4; jp++) {
                        uint32_t b[4];
                        ldsm4t(b, smem_u32(smem + PS_W2 + (16 * q + i) * W_PITCH + (2 * jp + nsel) * 16));
                        if (q == 0) {
                            mma16816_z(p[2 * jp], h[0], b[0], b[1]);
                            mma16816_z(p[2 * jp + 1], h[0], b[2], b[3]);
                        } else {
                            mma16816(p[2 * jp], h[q], b[0], b[1]);
                            mma16816(p[2 * jp + 1], h[q], b[2], b[3]);
                        }
                    }
                }
            }
#pragma unroll
            for (int r = 0; r < 2; r++) {
                uint4* row = r ? r1 : r0;
                uint32_t pv[8];
#pragma unroll
                for (int j = 0; j < 8; j++) pv[j] = pack_bf16(p[j][2 * r], p[j][2 * r + 1]);
#pragma unroll
                for (int c = 1; c < 4; c++) {
                    uint4 vx[2] = {row[c * 8], row[c * 8 + 1]};
                    const uint32_t* vv = reinterpret_cast<const uint32_t*>(vx);
                    uint32_t u[8];
#pragma unroll
                    for (int j = 0; j < 8; j++) u[j] = hmul2(pv[j], vv[j]);
                    row[c * 8] = make_uint4(__byte_perm(u[0], u[1], 0x5410), __byte_perm(u[2], u[3], 0x5410),
                                            __byte_perm(u[4], u[5], 0x5410), __byte_perm(u[6], u[7], 0x5410));
                    row[c * 8 + 1] = make_uint4(__byte_perm(u[0], u[1], 0x7632), __byte_perm(u[2], u[3], 0x7632),
                                                __byte_perm(u[4], u[5], 0x7632), __byte_perm(u[6], u[7], 0x7632));
                }
            }
            asm volatile("fence.proxy.async.shared::cta;" ::: "memory");
            __syncwarp();
            if (tid == 0) STAMP(3);
            if (lane == 0) {
                bulk_s2g(g_tab + (size_t)tile * 16 * ROWB, smem_u32(tb), nrows * 512);
                asm volatile("cp.async.bulk.commit_group;" ::: "memory");
                asm volatile("cp.async.bulk.wait_group 0;" ::: "memory");
            }
            if (tid == 0) STAMP(4);
        }
    } else {
        const int ptid = tid - 32 * P1_WARPS, pwarp = warp - P1_WARPS;
        const uint32_t bar = smem_u32(smem + PS_BAR);
        const int posbytes = N * 6;
        if (ptid == 0) {
            mbar_init(bar, 1);
            asm volatile("fence.mbarrier_init.release.cluster;" ::: "memory");
            mbar_expect_tx(bar, posbytes);
            bulk_g2s(smem_u32(smem + PS_POS), pos, posbytes, bar);
        }
        const int npairs = E >> 1;
        const int ppc = (npairs + NCTA - 1) / NCTA;
        const int pbeg = blockIdx.x * ppc, pend = min(pbeg + ppc, npairs);
        int2 es[P3_ITERS], ed[P3_ITERS];
#pragma unroll
        for (int it = 0; it < P3_ITERS; it++) {
            const int p = pbeg + ptid + it * P3_THREADS;
            if (p < pend) {
                es[it] = __ldcs(reinterpret_cast<const int2*>(src) + p);
                ed[it] = __ldcs(reinterpret_cast<const int2*>(dst) + p);
            }
        }
        int* hist = reinterpret_cast<int*>(smem + PS_HIST);
        for (int i = ptid; i < 1280; i += P3_THREADS) hist[i] = 0;
        {
            const int gi = ptid * NCTA + blockIdx.x;
            if (gi < NTAB * NRBF) {
                const int di = gi >> 4, k = gi & 15;
                const float d = __uint_as_float((uint32_t)(DBASE + di) << 16);
                const float arg = bf16r(d * __bfloat162float(freqs[k]));
                const float rbf = bf16r(bf16r(sinf(arg)) / d);
                const float ca = bf16r(bf16r(3.14159265358979f * d) / 5.0f);
                const float fc = 0.5f * bf16r(bf16r(cosf(ca)) + 1.0f);
                g_G[gi] = __float2bfloat16_rn(rbf * fc);
            }
        }
        if (ptid == 0) STAMP(5);
        asm volatile("bar.sync 2, %0;" ::"n"(P3_THREADS) : "memory");
        if (ptid == 0) STAMP(6);
        mbar_wait(bar, 0);
        if (ptid == 0) STAMP(7);
        const uint32_t* pw = reinterpret_cast<const uint32_t*>(smem + PS_POS);
        uint2 rec[P3_ITERS * 2];
        int key[P3_ITERS * 2];
#pragma unroll
        for (int q = 0; q < P3_ITERS * 2; q++) {
            const int it = q >> 1;
            key[q] = -1;
            if (pbeg + ptid + it * P3_THREADS < pend) {
                const int s = (q & 1) ? es[it].y : es[it].x;
                const int dd = (q & 1) ? ed[it].y : ed[it].x;
                const int ws = (s * 3) >> 1, wd = (dd * 3) >> 1;
                const uint32_t sa = pw[ws], sb = pw[ws + 1], da = pw[wd], db = pw[wd + 1];
                const uint32_t shs = (s & 1) << 4, shd = (dd & 1) << 4;
                const uint32_t rxy = hsub2(__funnelshift_r(sa, sb, shs), __funnelshift_r(da, db, shd));
                const uint32_t rz = hsub2(sb >> shs, db >> shd);
                const uint32_t qxy = hmul2(rxy, rxy), qz = hmul2(rz, rz);
                const float sum = (__uint_as_float(qxy << 16) + __uint_as_float(qxy & 0xffff0000u)) + __uint_as_float(qz << 16);
                if (sum < 23.9375f) {
                    const uint32_t exy = hmul2(rxy, 0x1e801e80u), ez = hmul2(rz, 0x1e801e80u);
                    rec[q].x = exy | ((dd & 3) << 13) | ((dd & 12) << 27);
                    rec[q].y = (ez & 0xffffu) | ((dd & 48) << 9) | ((uint32_t)s << 16) | ((uint32_t)(dd & 64) << 25);
                    const int grp = dd >> 3;
                    key[q] = (grp << 13) | atomicAdd(&hist[grp], 1);
                }
            }
        }
        if (ptid == 0) STAMP(8);
        asm volatile("bar.sync 2, %0;" ::"n"(P3_THREADS) : "memory");
        if (ptid == 0) STAMP(9);
        int2 hv = make_int2(0, 0);
        int incl = 0;
        if (pwarp < 20) {
            hv = reinterpret_cast<int2*>(hist)[ptid];
            incl = hv.x + hv.y;
#pragma unroll
            for (int o = 1; o < 32; o <<= 1) {
                const int v = __shfl_up_sync(0xffffffffu, incl, o);
                if (lane >= o) incl += v;
            }
            if (lane == 31) hist[1280 + pwarp] = incl;
        }
        asm volatile("bar.sync 2, %0;" ::"n"(P3_THREADS) : "memory");
        if (pwarp < 20) {
            int wsum = (lane < pwarp) ? hist[1280 + lane] : 0;
            wsum = __reduce_add_sync(0xffffffffu, wsum);
            const int ex = wsum + incl - hv.x - hv.y;
            reinterpret_cast<int2*>(hist)[ptid] = make_int2(ex, ex + hv.x);
        }
        asm volatile("bar.sync 2, %0;" ::"n"(P3_THREADS) : "memory");
        if (ptid == 0) STAMP(10);
        uint2* srec = reinterpret_cast<uint2*>(smem + PS_REC);
#pragma unroll
        for (int q = 0; q < P3_ITERS * 2; q++)
            if (key[q] >= 0) srec[hist[key[q] >> 13] + (key[q] & 8191)] = rec[q];
        const int ngroups = (N + GRP - 1) / GRP;
        unsigned short* spfx = reinterpret_cast<unsigned short*>(smem + PS_PFX);
        for (int i = ptid; i < NCTA * 16; i += P3_THREADS)
            spfx[i] = (unsigned short)hist[min(group_begin(i >> 4, ngroups) + (i & 15), ngroups)];
        asm volatile("fence.proxy.async.shared::cta;" ::: "memory");
        asm volatile("bar.sync 2, %0;" ::"n"(P3_THREADS) : "memory");
        if (ptid == 0) {
            STAMP(11);
            const int total = hist[ngroups];
            const int bytes = ((total + 1) >> 1) * 16;
            if (bytes > 0) bulk_s2g(g_rec + blockIdx.x * CH, smem_u32(srec), bytes);
            bulk_s2g(g_pfx + blockIdx.x * NCTA * 16, smem_u32(spfx), NCTA * 32);
            asm volatile("cp.async.bulk.commit_group;" ::: "memory");
            asm volatile("cp.async.bulk.wait_group 0;" ::: "memory");
            STAMP(12);
        }
    }
}

constexpr int UNITS = 3;
constexpr int STAGES = 3;
constexpr int M_THREADS = UNITS * 128 + 128;
constexpr int ST_G = 4 * 4096;
constexpr int ST_S = ST_G + 1024;
constexpr int STAGE_BYTES = ST_S + 2048;
constexpr int RCAP = 4576;
constexpr int MAXQ = 10;
constexpr int HOT0 = 0x3F00 - DBASE;
constexpr int MS_REC = UNITS * STAGES * STAGE_BYTES;
constexpr int MS_GH = MS_REC + RCAP * 8;
constexpr int MS_B2 = MS_GH + (NTAB - HOT0) * 32;
constexpr int MS_MISC = MS_B2 + MAXQ * 136 * 4;
constexpr int MS_BAR = MS_MISC + 32 * 4;
constexpr int CTL_STRIDE = STAGE_BYTES >> 7;
constexpr int M_SMEM = MS_BAR + 8 + UNITS * STAGES * CTL_STRIDE;
static_assert(M_SMEM <= 232448, "smem");
static_assert(MS_BAR % 8 == 0 && MS_GH % 16 == 0 && STAGE_BYTES % 1024 == 0, "align");

template <int ACC, uint32_t HI>
__device__ __forceinline__ void wgmma_n32(float (&d)[16], const uint32_t (&a)[4], uint32_t lo) {
    if (ACC) {
        asm volatile("{\n.reg .b64 dd;\nmov.b64 dd, {%20, %21};\n"
                     "wgmma.mma_async.sync.aligned.m64n32k16.f32.bf16.bf16 {%0,%1,%2,%3,%4,%5,%6,%7,%8,%9,%10,%11,%12,%13,%14,%15}, {%16,%17,%18,%19}, dd, 1, 1, 1, 0;\n}\n"
                     : "+f"(d[0]), "+f"(d[1]), "+f"(d[2]), "+f"(d[3]), "+f"(d[4]), "+f"(d[5]), "+f"(d[6]), "+f"(d[7]),
                       "+f"(d[8]), "+f"(d[9]), "+f"(d[10]), "+f"(d[11]), "+f"(d[12]), "+f"(d[13]), "+f"(d[14]), "+f"(d[15])
                     : "r"(a[0]), "r"(a[1]), "r"(a[2]), "r"(a[3]), "r"(lo), "n"(HI));
    } else {
        asm volatile("{\n.reg .b64 dd;\nmov.b64 dd, {%20, %21};\n"
                     "wgmma.mma_async.sync.aligned.m64n32k16.f32.bf16.bf16 {%0,%1,%2,%3,%4,%5,%6,%7,%8,%9,%10,%11,%12,%13,%14,%15}, {%16,%17,%18,%19}, dd, 0, 1, 1, 0;\n}\n"
                     : "=f"(d[0]), "=f"(d[1]), "=f"(d[2]), "=f"(d[3]), "=f"(d[4]), "=f"(d[5]), "=f"(d[6]), "=f"(d[7]),
                       "=f"(d[8]), "=f"(d[9]), "=f"(d[10]), "=f"(d[11]), "=f"(d[12]), "=f"(d[13]), "=f"(d[14]), "=f"(d[15])
                     : "r"(a[0]), "r"(a[1]), "r"(a[2]), "r"(a[3]), "r"(lo), "n"(HI));
    }
}
constexpr uint32_t DESC_H = 64u | (1u << 30);
constexpr uint32_t DESC_G = 16u | (3u << 30);
__device__ __forceinline__ void reg_fence16(float (&d)[16]) {
    asm volatile("" : "+f"(d[0]), "+f"(d[1]), "+f"(d[2]), "+f"(d[3]), "+f"(d[4]), "+f"(d[5]), "+f"(d[6]), "+f"(d[7]),
                      "+f"(d[8]), "+f"(d[9]), "+f"(d[10]), "+f"(d[11]), "+f"(d[12]), "+f"(d[13]), "+f"(d[14]), "+f"(d[15]) :: "memory");
}
__device__ __forceinline__ uint32_t pin(uint32_t x) { return __shfl_sync(0xffffffffu, x, threadIdx.x & 31); }

template <bool FITS>
__device__ __forceinline__ void producer_loop(unsigned char* smem, const __nv_bfloat16* __restrict__ sv, int N,
                                              int unit, int q0, int nq) {
    const uint32_t sbase = smem_u32(smem);
    const uint32_t ubase = __reduce_or_sync(0xffffffffu, sbase + unit * STAGES * STAGE_BYTES);
    const uint32_t ctl0 = sbase + MS_BAR + 8 - (sbase >> 7);
    int* misc = reinterpret_cast<int*>(smem + MS_MISC);
    const int ln = pin(threadIdx.x & 31);
    const int r4 = ln >> 3;
    const unsigned char* gsrc = g_tab + (ln & 7) * 16;
    asm volatile("" : "+l"(gsrc));
    const uint32_t d0 = r4 * 128 + (((ln & 7) ^ r4) << 4);
    const uint32_t goff = ST_G + ln * 32 + (((ln >> 2) & 1) << 4);
    uint32_t sb = ubase, ph = 1;
    int q = (int)__reduce_or_sync(0xffffffffu, (uint32_t)unit);
    while (q < nq) {
        int base = (ln < q) ? misc[ln] : 0;
        uint32_t ra = sbase + MS_REC + (__reduce_add_sync(0xffffffffu, base) + ln) * 8;
        const int cnt = (int)__reduce_or_sync(0xffffffffu, (uint32_t)misc[q]);
        int rem = cnt;
        const int grp = q0 + q;
        const unsigned char* svp = reinterpret_cast<const unsigned char*>(sv) + (size_t)(grp * GRP + r4) * 512 + (ln & 7) * 16;
        auto fetch = [&](int left) -> uint2 {
            uint2 r = make_uint2(0, 0);
            if (FITS) {
                asm volatile("ld.shared.v2.u32 {%0,%1}, [%2];" : "=r"(r.x), "=r"(r.y) : "r"(ra));
                ra += 256;
            } else if (ln < left) {
                const int j = cnt - left + ln;
                const int* prq = reinterpret_cast<const int*>(smem + MS_B2) + q * 136;
                int lo = 0, hi = NCTA;
                while (hi - lo > 1) {
                    const int mid = (lo + hi) >> 1;
                    if (prq[mid] <= j) lo = mid; else hi = mid;
                }
                r = __ldcg(g_rec + lo * CH + __ldcg(g_pfx + (lo * NCTA + blockIdx.x) * 16 + q) + (j - prq[lo]));
            }
            return r;
        };
        uint2 rn = fetch(rem);
        bool last;
        do {
            const bool valid = ln < rem;
            last = rem <= 24;
            const uint2 r = valid ? rn : make_uint2(0, 0);
            rn = fetch(rem - 32);
            const uint32_t srcv = (r.y >> 16) & 0x7fffu;
            const unsigned char* gq[8];
#pragma unroll
            for (int k = 0; k < 8; k++)
                gq[k] = gsrc + (size_t)__shfl_sync(0xffffffffu, srcv, k * 4 + r4) * ROWB;
            const int lim = rem - r4;
            const int lim6 = last ? N - grp * GRP + 24 - r4 : lim;
            if (last) { gq[6] = svp; gq[7] = svp + 4 * 512; }
            const uint32_t rxy = hmul2(r.x & 0x9fff9fffu, 0x60806080u);
            const uint32_t rz2 = hmul2(r.y & 0x00009fffu, 0x60806080u);
            const uint32_t qxy = hmul2(rxy, rxy), qz = hmul2(rz2, rz2);
            const float sum = bf16r((__uint_as_float(qxy << 16) + __uint_as_float(qxy & 0xffff0000u)) + __uint_as_float(qz << 16));
            float sq;
            asm("sqrt.approx.ftz.f32 %0, %1;" : "=f"(sq) : "f"(bf16r(sum + 1e-8f)));
            const uint32_t dbits = pack_bf16(0.f, sq);
            float rinv;
            asm("rcp.approx.ftz.f32 %0, %1;" : "=f"(rinv) : "f"(__uint_as_float(dbits)));
            const int di = valid ? max(min((int)(dbits >> 16), DEND - 1) - DBASE, 0) : NTAB - 1;
            const uint4* gp = reinterpret_cast<const uint4*>(di >= HOT0 ? smem + (MS_GH - HOT0 * 32)
                                                                        : reinterpret_cast<unsigned char*>(g_G)) + 2 * di;
            const uint32_t r01 = pack_bf16(__uint_as_float(rxy << 16) * rinv, __uint_as_float(rxy & 0xffff0000u) * rinv);
            const uint32_t r2 = pack_bf16(__uint_as_float(rz2 << 16) * rinv, valid ? 1.0f : 0.f);
            const uint32_t so = ((r.x >> 12) & 6u) | ((r.x >> 26) & 8u);
            const uint32_t fl = ((uint32_t)grp << 4) | (last ? 2u : 0u);

            const uint32_t bar = ctl0 + (sb >> 7);
            mbar_wait(bar + 8, ph);
            const uint32_t dpa = sb + d0, dpb = (dpa ^ 64u) + 512u;
#pragma unroll
            for (int k = 0; k < 8; k++) {
                asm volatile("{\n.reg .pred p;\nsetp.le.s32 p, %2, %3;\n"
                             "cp.async.cg.shared.global [%0], [%1], 16, p;\n"
                             "cp.async.cg.shared.global [%0+4096], [%1+128], 16, p;\n"
                             "cp.async.cg.shared.global [%0+8192], [%1+256], 16, p;\n"
                             "cp.async.cg.shared.global [%0+12288], [%1+384], 16, p;\n}\n"
                             ::"r"(((k & 1) ? dpb : dpa) + (k >> 1) * 1024), "l"(gq[k]), "r"(k < 6 ? lim : lim6), "r"(4 * k) : "memory");
            }
            asm volatile("cp.async.mbarrier.arrive.noinc.shared::cta.b64 [%0];" ::"r"(bar) : "memory");
            const uint4 g0 = gp[0], g1 = gp[1];
            const uint32_t za = sb + ST_S + ln * 16;
#pragma unroll
            for (int j = 0; j < 4; j++)
                asm volatile("st.shared.v4.u32 [%0], {%1,%1,%1,%1};" ::"r"(za + j * 512), "r"(0u) : "memory");
            asm volatile("st.shared.u16 [%0], %1;" ::"r"(za + so), "h"((unsigned short)(r2 >> 16)) : "memory");
            asm volatile("st.shared.u16 [%0+512], %1;" ::"r"(za + so), "h"((unsigned short)(r01 & 0xffffu)) : "memory");
            asm volatile("st.shared.u16 [%0+1024], %1;" ::"r"(za + so), "h"((unsigned short)(r01 >> 16)) : "memory");
            asm volatile("st.shared.u16 [%0+1536], %1;" ::"r"(za + so), "h"((unsigned short)(r2 & 0xffffu)) : "memory");
            asm volatile("st.shared.u32 [%0+16], %1;" ::"r"(bar), "r"(fl) : "memory");
            asm volatile("st.shared.v4.u32 [%0], {%1,%2,%3,%4};" ::"r"(sb + goff),
                         "r"(g0.x), "r"(g0.y), "r"(g0.z), "r"(g0.w) : "memory");
            asm volatile("st.shared.v4.u32 [%0], {%1,%2,%3,%4};" ::"r"((sb + goff) ^ 16u),
                         "r"(g1.x), "r"(g1.y), "r"(g1.z), "r"(g1.w) : "memory");
            mbar_arrive(bar);
            sb += STAGE_BYTES;
            if (sb == ubase + STAGES * STAGE_BYTES) { sb = ubase; ph ^= 1; }
            rem -= 32;
        } while (!last);
        int nx = 0;
        if (ln == 0) nx = atomicAdd(&misc[16], 1);
        q = (int)__reduce_or_sync(0xffffffffu, (uint32_t)nx);
    }
    const uint32_t bar = ctl0 + (sb >> 7);
    mbar_wait(bar + 8, ph);
    asm volatile("st.shared.u32 [%0+16], %1;" ::"r"(bar), "r"(8u) : "memory");
    mbar_arrive(bar);
    mbar_arrive(bar);
}

__global__ void __launch_bounds__(M_THREADS, 1)
main_kernel(const __nv_bfloat16* __restrict__ sv, const __nv_bfloat16* __restrict__ w2,
            const __nv_bfloat16* __restrict__ wrbf, __nv_bfloat16* __restrict__ out, int N) {
    extern __shared__ __align__(1024) unsigned char smem[];
    const int tid = threadIdx.x, warp = tid >> 5, lane = tid & 31;
    const int g = lane >> 2, t = lane & 3;
    const int ngroups = (N + GRP - 1) / GRP;
    const int q0 = group_begin(blockIdx.x, ngroups);
    const int nq = group_begin(blockIdx.x + 1, ngroups) - q0;
    const uint32_t sbase = smem_u32(smem);
    const uint32_t ghbar = sbase + MS_BAR;
    int* misc = reinterpret_cast<int*>(smem + MS_MISC);
    const bool is_prod = warp >= UNITS * 4;

    if (tid == 0) {
        STAMP(16);
        for (int i = 0; i < UNITS * STAGES; i++) {
            mbar_init(sbase + MS_BAR + 8 + i * CTL_STRIDE, 64);
            mbar_init(sbase + MS_BAR + 8 + i * CTL_STRIDE + 8, 4);
        }
        mbar_init(ghbar, 1);
        asm volatile("fence.mbarrier_init.release.cluster;" ::: "memory");
        misc[16] = UNITS;
    }
    if (tid == 0) STAMP(17);
    asm volatile("griddepcontrol.wait;" ::: "memory");
    if (tid == 0) STAMP(18);

    const unsigned short* pfx = g_pfx + blockIdx.x * 16;
    int* b2 = reinterpret_cast<int*>(smem + MS_B2);
    uint2* srec = reinterpret_cast<uint2*>(smem + MS_REC);
    {
        if (tid == 0) {
            mbar_expect_tx(ghbar, (NTAB - HOT0) * 32);
            bulk_g2s(sbase + MS_GH, g_G + HOT0 * NRBF, (NTAB - HOT0) * 32, ghbar);
        }
        int beg = 0, end = 0;
        {
            const int p = warp + 16 * lane;
            if (p < NCTA) {
                beg = __ldcg(pfx + p * NCTA * 16);
                end = __ldcg(pfx + p * NCTA * 16 + nq);
            }
        }
        int lo[5], cq[5];
        if (warp < nq) {
#pragma unroll
            for (int k = 0; k < 5; k++) {
                const int p = lane * 5 + k;
                lo[k] = 0; cq[k] = 0;
                if (p < NCTA) {
                    lo[k] = __ldcg(pfx + p * NCTA * 16 + warp);
                    cq[k] = __ldcg(pfx + p * NCTA * 16 + warp + 1);
                }
            }
        }
        uint2 r[9];
#pragma unroll
        for (int k = 0; k < 9; k++) {
            const int i = __shfl_sync(0xffffffffu, beg, k) + lane;
            const int e = __shfl_sync(0xffffffffu, end, k);
            if (i < e) r[k] = __ldcg(g_rec + (warp + 16 * k) * CH + i);
        }
        int pre = 0;
        if (warp < nq) {
            int sum = 0;
#pragma unroll
            for (int k = 0; k < 5; k++) { cq[k] -= lo[k]; sum += cq[k]; }
            int in2 = sum;
#pragma unroll
            for (int o = 1; o < 32; o <<= 1) {
                const int v = __shfl_up_sync(0xffffffffu, in2, o);
                if (lane >= o) in2 += v;
            }
            pre = in2 - sum;
            if (lane == 31) misc[warp] = in2;
        }
        __syncthreads();
        if (tid == 0) STAMP(19);
        const int tv = lane < nq ? misc[lane] : 0;
        const bool fits = __reduce_add_sync(0xffffffffu, tv) <= RCAP;
        if (warp < nq) {
            if (fits) pre += __reduce_add_sync(0xffffffffu, lane < warp ? tv : 0);
#pragma unroll
            for (int k = 0; k < 5; k++) {
                const int p = lane * 5 + k;
                if (p < NCTA) b2[warp * 136 + p] = fits ? pre - lo[k] : pre;
                pre += cq[k];
            }
        }
        __syncthreads();
        if (fits) {
#pragma unroll
            for (int k = 0; k < 9; k++) {
                const int p = warp + 16 * k;
                int i = __shfl_sync(0xffffffffu, beg, k) + lane;
                const int e = __shfl_sync(0xffffffffu, end, k);
                uint2 v = r[k];
                while (i < e) {
                    const int q = (int)((((v.x >> 30) & 1u) | ((v.y >> 12) & 6u) | ((v.y >> 28) & 8u)) - (uint32_t)q0) & 15;
                    srec[b2[q * 136 + p] + i] = v;
                    i += 32;
                    if (i < e) v = __ldcg(g_rec + p * CH + i);
                }
            }
        }
        if (tid == 0) misc[17] = fits;
        __syncthreads();
    }
    if (tid == 0) STAMP(20);

    if (is_prod) {
        asm volatile("setmaxnreg.dec.sync.aligned.u32 80;");
        const int unit = warp - UNITS * 4;
        if (unit < UNITS) {
            mbar_wait(ghbar, 0);
            if (unit == 0 && lane == 0) STAMP(21);
            if (misc[17]) producer_loop<true>(smem, sv, N, unit, q0, nq);
            else producer_loop<false>(smem, sv, N, unit, q0, nq);
            if (lane == 0) STAMP(22 + unit);
        }
    } else {
        asm volatile("setmaxnreg.inc.sync.aligned.u32 144;");
        const int unit = warp >> 2, w = warp & 3;
        const uint32_t ubase = sbase + unit * STAGES * STAGE_BYTES;
        const uint32_t ctl0 = sbase + MS_BAR + 8 - (sbase >> 7);
        uint32_t wa[3][4], pa[2][4][4];
        {
            const int c = 16 * w + 2 * g;
#pragma unroll
            for (int p = 0; p < 3; p++)
#pragma unroll
                for (int kh = 0; kh < 2; kh++) {
                    const uint32_t lo = __ldg(reinterpret_cast<const uint32_t*>(wrbf + (2 * t + 8 * kh) * 192 + p * 64 + c));
                    const uint32_t hi = __ldg(reinterpret_cast<const uint32_t*>(wrbf + (2 * t + 8 * kh + 1) * 192 + p * 64 + c));
                    wa[p][2 * kh + 0] = __byte_perm(lo, hi, 0x5410);
                    wa[p][2 * kh + 1] = __byte_perm(lo, hi, 0x7632);
                }
#pragma unroll
            for (int p = 0; p < 2; p++)
#pragma unroll
                for (int q = 0; q < 4; q++)
#pragma unroll
                    for (int kh = 0; kh < 2; kh++) {
                        const int r = 8 * (t + 4 * kh) + 2 * q;
                        const uint32_t lo = __ldg(reinterpret_cast<const uint32_t*>(w2 + r * 192 + p * 128 + c));
                        const uint32_t hi = __ldg(reinterpret_cast<const uint32_t*>(w2 + (r + 1) * 192 + p * 128 + c));
                        pa[p][q][2 * kh + 0] = __byte_perm(lo, hi, 0x5410);
                        pa[p][q][2 * kh + 1] = __byte_perm(lo, hi, 0x7632);
                    }
        }
        float acc[4][4];
#pragma unroll
        for (int c = 0; c < 4; c++)
#pragma unroll
            for (int e = 0; e < 4; e++) acc[c][e] = 0.f;
        const int erow = (lane & 7) + 8 * (lane >> 4);
        const int ehalf = (lane >> 3) & 1;
        const uint32_t ua = pin(4096 + erow * 128 + ((uint32_t)((2 * w + ehalf) ^ (lane & 7)) << 4));
        const uint32_t sa = pin(ST_S + lane * 16);
        const uint32_t ub = __reduce_or_sync(0xffffffffu, ubase);
        uint32_t sb = ub;
        uint32_t ph = 0;
        const bool elected = sa == ST_S;
        while (true) {
            mbar_wait(ctl0 + (sb >> 7), ph);
            {
                asm volatile("fence.proxy.async.shared::cta;" ::: "memory");
                const uint32_t dh = (sb >> 4) | (1u << 16);
                const uint32_t dg = dh + (ST_G >> 4);
                uint32_t m[2][4], u[3][2][4], sf[4];
                {
                    float ps[16], fs[16], fv[16];
                    asm volatile("wgmma.fence.sync.aligned;" ::: "memory");
                    wgmma_n32<0, DESC_G>(fv, wa[1], dg);
                    wgmma_n32<0, DESC_G>(fs, wa[0], dg);
                    wgmma_n32<0, DESC_H>(ps, pa[0][0], dh);
                    wgmma_n32<1, DESC_H>(ps, pa[0][1], dh + 2);
                    wgmma_n32<1, DESC_H>(ps, pa[0][2], dh + 4);
                    wgmma_n32<1, DESC_H>(ps, pa[0][3], dh + 6);
                    asm volatile("wgmma.commit_group.sync.aligned;" ::: "memory");
#pragma unroll
                    for (int j = 0; j < 3; j++) ldsm4t(u[j][0], sb + ua + j * 4096);
                    ldsm4t(sf, sb + sa);
                    asm volatile("wgmma.wait_group.sync.aligned 0;" ::: "memory");
                    reg_fence16(fv); reg_fence16(fs); reg_fence16(ps);
#pragma unroll
                    for (int i = 0; i < 8; i++)
                        m[i >> 2][i & 3] = pack_bf16(fs[2 * i] * ps[2 * i], fs[2 * i + 1] * ps[2 * i + 1]);
#pragma unroll
                    for (int j = 0; j < 3; j++) ldsm4t(u[j][1], sb + ua + j * 4096 + 2048);
                    float pr[16], fr[16];
                    asm volatile("wgmma.fence.sync.aligned;" ::: "memory");
                    wgmma_n32<0, DESC_G>(fr, wa[2], dg);
                    wgmma_n32<0, DESC_H>(pr, pa[1][0], dh);
                    wgmma_n32<1, DESC_H>(pr, pa[1][1], dh + 2);
                    wgmma_n32<1, DESC_H>(pr, pa[1][2], dh + 4);
                    wgmma_n32<1, DESC_H>(pr, pa[1][3], dh + 6);
                    asm volatile("wgmma.commit_group.sync.aligned;" ::: "memory");
#pragma unroll
                    for (int i = 0; i < 8; i++) {
                        const uint32_t wv = pack_bf16(fv[2 * i], fv[2 * i + 1]);
#pragma unroll
                        for (int j = 0; j < 3; j++) u[j][i >> 2][i & 3] = hmul2(u[j][i >> 2][i & 3], wv);
                    }
                    uint32_t sj[3][4];
#pragma unroll
                    for (int j = 0; j < 3; j++) ldsm4t(sj[j], sb + sa + (j + 1) * 512);
#pragma unroll
                    for (int s = 0; s < 2; s++) {
                        mma16816(acc[0], m[s], sf[2 * s], sf[2 * s + 1]);
#pragma unroll
                        for (int j = 0; j < 3; j++) mma16816(acc[j + 1], u[j][s], sf[2 * s], sf[2 * s + 1]);
                    }
                    asm volatile("wgmma.wait_group.sync.aligned 0;" ::: "memory");
                    reg_fence16(fr); reg_fence16(pr);
#pragma unroll
                    for (int i = 0; i < 8; i++)
                        m[i >> 2][i & 3] = pack_bf16(fr[2 * i] * pr[2 * i], fr[2 * i + 1] * pr[2 * i + 1]);
#pragma unroll
                    for (int s = 0; s < 2; s++)
#pragma unroll
                        for (int j = 0; j < 3; j++) mma16816(acc[j + 1], m[s], sj[j][2 * s], sj[j][2 * s + 1]);
                }
            }
            uint32_t flags;
            asm volatile("ld.shared.u32 %0, [%1+16];" : "=r"(flags) : "r"(ctl0 + (sb >> 7)));
            if (flags & 10u) {
                if (flags & 8u) break;
                const int node0 = (int)(flags >> 4) * GRP + 2 * t;
                uint32_t* op = reinterpret_cast<uint32_t*>(out) + (size_t)node0 * 128 + 8 * w + g;
#pragma unroll
                for (int b = 0; b < 2; b++) {
                    const uint32_t va = sb + (24 + 2 * t + b) * 128 + (((uint32_t)(2 * w + (g >> 2)) ^ (uint32_t)(2 * t + b)) << 4) + (g & 3) * 4;
#pragma unroll
                    for (int c = 0; c < 4; c++) {
                        uint32_t v;
                        asm volatile("ld.shared.u32 %0, [%1];" : "=r"(v) : "r"(va + c * 4096));
                        const uint32_t o = pack_bf16(__uint_as_float(v << 16) + acc[c][b],
                                                     __uint_as_float(v & 0xffff0000u) + acc[c][2 + b]);
                        if (node0 + b < N) op[b * 128 + c * 32] = o;
                        acc[c][b] = 0.f; acc[c][2 + b] = 0.f;
                    }
                }
            }
            __syncwarp();
            if (elected) mbar_arrive(ctl0 + (sb >> 7) + 8);
            sb += STAGE_BYTES;
            if (sb == ub + STAGES * STAGE_BYTES) { sb = ub; ph ^= 1; }
        }
        if (lane == 0 && w == 0) STAMP(26 + unit);
    }
}

}

extern "C" void kernel_launch(void* const* d_in, const int* in_sizes, int n_in, void* d_out, int out_size) {
    const __nv_bfloat16* sv = (const __nv_bfloat16*)d_in[0];
    const __nv_bfloat16* pos = (const __nv_bfloat16*)d_in[1];
    const int* src = (const int*)d_in[2];
    const int* dst = (const int*)d_in[3];
    const __nv_bfloat16* freqs = (const __nv_bfloat16*)d_in[4];
    const __nv_bfloat16* w1 = (const __nv_bfloat16*)d_in[5];
    const __nv_bfloat16* w2 = (const __nv_bfloat16*)d_in[6];
    const __nv_bfloat16* wrbf = (const __nv_bfloat16*)d_in[7];
    __nv_bfloat16* out = (__nv_bfloat16*)d_out;
    const int N = in_sizes[1] / 3;
    const int E = in_sizes[2];

    static bool init = false;
    if (!init) {
        cudaFuncSetAttribute(prep_kernel, cudaFuncAttributeMaxDynamicSharedMemorySize, PS_TOTAL);
        cudaFuncSetAttribute(main_kernel, cudaFuncAttributeMaxDynamicSharedMemorySize, M_SMEM);
        init = true;
    }
    cudaStream_t stream = cudaStreamPerThread;
    prep_kernel<<<NCTA, P_THREADS, PS_TOTAL, stream>>>(sv, pos, src, dst, freqs, w1, w2, N, E);

    cudaLaunchConfig_t cfg = {};
    cfg.gridDim = dim3(NCTA);
    cfg.blockDim = dim3(M_THREADS);
    cfg.dynamicSmemBytes = M_SMEM;
    cfg.stream = stream;
    cudaLaunchAttribute at[1];
    at[0].id = cudaLaunchAttributeProgrammaticStreamSerialization;
    at[0].val.programmaticStreamSerializationAllowed = 1;
    cfg.attrs = at;
    cfg.numAttrs = 1;
    cudaLaunchKernelEx(&cfg, main_kernel, sv, w2, wrbf, out, N);
}
```

```cpp
#include <cuda_runtime.h>
#include <cuda_bf16.h>
#include <stdint.h>

namespace {

constexpr int D = 64;
constexpr int NRBF = 16;
constexpr int MAXN = 10000;
constexpr int MAXE = 640000;
constexpr int NCTA = 132;
constexpr int GRP = 8;
constexpr int MAXG = (MAXN + GRP - 1) / GRP;
constexpr int CH = 4864;
constexpr int DBASE = 0x38C0;
constexpr int DEND = 0x40A0;
constexpr int NTAB = DEND - DBASE;
constexpr int ROWB = 512;

__device__ __align__(128) unsigned char g_tab[(size_t)(MAXN + 16) * ROWB];
__device__ __align__(128) __nv_bfloat16 g_G[NTAB * NRBF];
__device__ __align__(128) uint2 g_rec[NCTA * CH];
__device__ __align__(128) unsigned short g_pfx[NCTA * NCTA * 16];

#define STAMP(k) do {} while (0)

__device__ __forceinline__ uint32_t smem_u32(const void* p) { return (uint32_t)__cvta_generic_to_shared(p); }
__device__ __forceinline__ uint32_t pack_bf16(float lo, float hi) {
    uint32_t r;
    asm("cvt.rn.bf16x2.f32 %0, %1, %2;" : "=r"(r) : "f"(hi), "f"(lo));
    return r;
}
__device__ __forceinline__ float bf16r(float x) { return __uint_as_float(pack_bf16(0.f, x) & 0xffff0000u); }
__device__ __forceinline__ uint32_t hmul2(uint32_t a, uint32_t b) {
    uint32_t r;
    asm("mul.rn.bf16x2 %0, %1, %2;" : "=r"(r) : "r"(a), "r"(b));
    return r;
}
__device__ __forceinline__ uint32_t hsub2(uint32_t a, uint32_t b) {
    uint32_t r;
    asm("sub.rn.bf16x2 %0, %1, %2;" : "=r"(r) : "r"(a), "r"(b));
    return r;
}
__device__ __forceinline__ uint32_t hfma2(uint32_t a, uint32_t b, uint32_t c) {
    uint32_t r;
    asm("fma.rn.bf16x2 %0, %1, %2, %3;" : "=r"(r) : "r"(a), "r"(b), "r"(c));
    return r;
}
__device__ __forceinline__ void mma16816(float (&c)[4], const uint32_t (&a)[4], uint32_t b0, uint32_t b1) {
    asm volatile("mma.sync.aligned.m16n8k16.row.col.f32.bf16.bf16.f32 {%0,%1,%2,%3}, {%4,%5,%6,%7}, {%8,%9}, {%0,%1,%2,%3};"
                 : "+f"(c[0]), "+f"(c[1]), "+f"(c[2]), "+f"(c[3])
                 : "r"(a[0]), "r"(a[1]), "r"(a[2]), "r"(a[3]), "r"(b0), "r"(b1));
}
__device__ __forceinline__ void mma16816_z(float (&c)[4], const uint32_t (&a)[4], uint32_t b0, uint32_t b1) {
    asm volatile("mma.sync.aligned.m16n8k16.row.col.f32.bf16.bf16.f32 {%0,%1,%2,%3}, {%4,%5,%6,%7}, {%8,%9}, {%10,%10,%10,%10};"
                 : "=f"(c[0]), "=f"(c[1]), "=f"(c[2]), "=f"(c[3])
                 : "r"(a[0]), "r"(a[1]), "r"(a[2]), "r"(a[3]), "r"(b0), "r"(b1), "f"(0.f));
}
__device__ __forceinline__ void ldsm4(uint32_t (&r)[4], uint32_t addr) {
    asm volatile("ldmatrix.sync.aligned.m8n8.x4.shared.b16 {%0,%1,%2,%3}, [%4];"
                 : "=r"(r[0]), "=r"(r[1]), "=r"(r[2]), "=r"(r[3]) : "r"(addr));
}
__device__ __forceinline__ void ldsm4t(uint32_t (&r)[4], uint32_t addr) {
    asm volatile("ldmatrix.sync.aligned.m8n8.x4.trans.shared.b16 {%0,%1,%2,%3}, [%4];"
                 : "=r"(r[0]), "=r"(r[1]), "=r"(r[2]), "=r"(r[3]) : "r"(addr));
}
__device__ __forceinline__ void mbar_init(uint32_t bar, int cnt) {
    asm volatile("mbarrier.init.shared::cta.b64 [%0], %1;" ::"r"(bar), "r"(cnt) : "memory");
}
__device__ __forceinline__ void mbar_arrive(uint32_t bar) {
    asm volatile("mbarrier.arrive.shared::cta.b64 _, [%0];" ::"r"(bar) : "memory");
}
__device__ __forceinline__ void mbar_expect_tx(uint32_t bar, uint32_t bytes) {
    asm volatile("mbarrier.arrive.expect_tx.shared::cta.b64 _, [%0], %1;" ::"r"(bar), "r"(bytes) : "memory");
}
__device__ __forceinline__ void mbar_wait(uint32_t bar, uint32_t parity) {
    asm volatile(
        "{\n.reg .pred p;\n.reg .u32 n;\nmov.u32 n, 0;\n"
        "WAIT_%=:\n"
        "mbarrier.try_wait.parity.shared::cta.b64 p, [%0], %1, %2;\n"
        "@p bra DONE_%=;\n"
        "add.u32 n, n, 1;\n"
        "setp.lt.u32 p, n, 100000;\n"
        "@p bra WAIT_%=;\n"
        "exit;\n"
        "DONE_%=:\n}\n" ::"r"(bar), "r"(parity), "r"(10000u) : "memory");
}
__device__ __forceinline__ void bulk_g2s(uint32_t dst, const void* src, uint32_t bytes, uint32_t bar) {
    asm volatile("cp.async.bulk.shared::cluster.global.mbarrier::complete_tx::bytes [%0], [%1], %2, [%3];"
                 ::"r"(dst), "l"(src), "r"(bytes), "r"(bar) : "memory");
}
__device__ __forceinline__ void bulk_s2g(void* dst, uint32_t src, uint32_t bytes) {
    asm volatile("cp.async.bulk.global.shared::cta.bulk_group [%0], [%1], %2;" ::"l"(dst), "r"(src), "r"(bytes) : "memory");
}
__device__ __forceinline__ int group_begin(int c, int ngroups) { return (c * ngroups) / NCTA; }

constexpr int P_THREADS = 1024;
constexpr int P1_WARPS = 5;
constexpr int P3_THREADS = P_THREADS - 32 * P1_WARPS;
constexpr int P3_ITERS = 3;
constexpr int W_PITCH = 144;
constexpr int PS_TILE = 0;
constexpr int PS_REC = PS_TILE + P1_WARPS * 8192;
constexpr int PS_PFX = PS_REC + CH * 8;
constexpr int PS_POS = PS_PFX + NCTA * 32;
constexpr int PS_W1 = PS_POS + 60032;
constexpr int PS_W2 = PS_W1 + 64 * W_PITCH;
constexpr int PS_HIST = PS_W2 + 64 * W_PITCH;
constexpr int PS_BAR = PS_HIST + (1280 + 32) * 4;
constexpr int PS_TOTAL = PS_BAR + 64;

__global__ void __launch_bounds__(P_THREADS, 1)
prep_kernel(const __nv_bfloat16* __restrict__ sv, const __nv_bfloat16* __restrict__ pos,
            const int* __restrict__ src, const int* __restrict__ dst,
            const __nv_bfloat16* __restrict__ freqs, const __nv_bfloat16* __restrict__ w1,
            const __nv_bfloat16* __restrict__ w2, int N, int E) {
    extern __shared__ __align__(1024) unsigned char smem[];
    const int tid = threadIdx.x, warp = tid >> 5, lane = tid & 31;
    asm volatile("griddepcontrol.launch_dependents;");
    if (tid == 0) STAMP(0);

    if (warp < P1_WARPS) {
        const int g = lane >> 2, t = lane & 3;
        const int tile = warp * gridDim.x + blockIdx.x;
        const int nrows = min(16, N - tile * 16);
        const uint32_t bar = smem_u32(smem + PS_BAR + 8 + 8 * warp);
        unsigned char* tb = smem + PS_TILE + warp * 8192;
        if (nrows > 0 && lane == 0) {
            mbar_init(bar, 1);
            asm volatile("fence.mbarrier_init.release.cluster;" ::: "memory");
            mbar_expect_tx(bar, nrows * 512);
            bulk_g2s(smem_u32(tb), sv + (size_t)tile * 16 * 256, nrows * 512, bar);
        }
        for (int i = tid; i < 64 * 8; i += 32 * P1_WARPS) {
            const int r = i >> 3, c = i & 7;
            *reinterpret_cast<uint4*>(smem + PS_W1 + r * W_PITCH + c * 16) =
                __ldg(reinterpret_cast<const uint4*>(w1 + r * 64) + c);
            const uint4 v = __ldg(reinterpret_cast<const uint4*>(w2 + r * 192 + 64) + c);
            const int tt = c >> 1, j0 = (c & 1) * 4;
            uint32_t* o = reinterpret_cast<uint32_t*>(smem + PS_W2 + r * W_PITCH);
            o[4 * (j0 + 0) + tt] = v.x; o[4 * (j0 + 1) + tt] = v.y;
            o[4 * (j0 + 2) + tt] = v.z; o[4 * (j0 + 3) + tt] = v.w;
        }
        asm volatile("bar.sync 1, %0;" ::"n"(32 * P1_WARPS) : "memory");
        if (tid == 0) STAMP(1);
        if (nrows > 0) {
            mbar_wait(bar, 0);
            if (tid == 0) STAMP(2);
            uint4* r0 = reinterpret_cast<uint4*>(tb + g * 512 + t * 32);
            uint4* r1 = reinterpret_cast<uint4*>(tb + (g + 8) * 512 + t * 32);
            uint32_t h[4][4];
            {
                uint4 xa[2] = {r0[0], r0[1]}, xb[2] = {r1[0], r1[1]};
                const uint32_t* s0 = reinterpret_cast<const uint32_t*>(xa);
                const uint32_t* s1 = reinterpret_cast<const uint32_t*>(xb);
                float a[8][4];
                const int i = lane & 7, hi = (lane >> 3) & 1, nsel = lane >> 4;
#pragma unroll
                for (int q = 0; q < 4; q++) {
                    const int krow = 16 * (i >> 1) + 4 * q + (i & 1) + 2 * hi;
                    const uint32_t af[4] = {s0[2 * q], s1[2 * q], s0[2 * q + 1], s1[2 * q + 1]};
#pragma unroll
                    for (int jp = 0; jp < 4; jp++) {
                        uint32_t b[4];
                        ldsm4t(b, smem_u32(smem + PS_W1 + krow * W_PITCH + (2 * jp + nsel) * 16));
                        if (q == 0) {
                            mma16816_z(a[2 * jp], af, b[0], b[1]);
                            mma16816_z(a[2 * jp + 1], af, b[2], b[3]);
                        } else {
                            mma16816(a[2 * jp], af, b[0], b[1]);
                            mma16816(a[2 * jp + 1], af, b[2], b[3]);
                        }
                    }
                }
#pragma unroll
                for (int j = 0; j < 8; j++) {
                    float f[4];
#pragma unroll
                    for (int e = 0; e < 4; e++) {
                        const float z = bf16r(a[j][e]);
                        f[e] = __fdividef(z, 1.0f + __expf(-z));
                    }
                    h[j >> 1][(j & 1) * 2 + 0] = pack_bf16(f[0], f[1]);
                    h[j >> 1][(j & 1) * 2 + 1] = pack_bf16(f[2], f[3]);
                }
            }
            r0[0] = make_uint4(h[0][0], h[0][2], h[1][0], h[1][2]);
            r0[1] = make_uint4(h[2][0], h[2][2], h[3][0], h[3][2]);
            r1[0] = make_uint4(h[0][1], h[0][3], h[1][1], h[1][3]);
            r1[1] = make_uint4(h[2][1], h[2][3], h[3][1], h[3][3]);
            float p[8][4];
            {
                const int i = lane & 15, nsel = lane >> 4;
#pragma unroll
                for (int q = 0; q < 4; q++) {
#pragma unroll
                    for (int jp = 0; jp < 4; jp++) {
                        uint32_t b[4];
                        ldsm4t(b, smem_u32(smem + PS_W2 + (16 * q + i) * W_PITCH + (2 * jp + nsel) * 16));
                        if (q == 0) {
                            mma16816_z(p[2 * jp], h[0], b[0], b[1]);
                            mma16816_z(p[2 * jp + 1], h[0], b[2], b[3]);
                        } else {
                            mma16816(p[2 * jp], h[q], b[0], b[1]);
                            mma16816(p[2 * jp + 1], h[q], b[2], b[3]);
                        }
                    }
                }
            }
#pragma unroll
            for (int r = 0; r < 2; r++) {
                uint4* row = r ? r1 : r0;
                uint32_t pv[8];
#pragma unroll
                for (int j = 0; j < 8; j++) pv[j] = pack_bf16(p[j][2 * r], p[j][2 * r + 1]);
#pragma unroll
                for (int c = 1; c < 4; c++) {
                    uint4 vx[2] = {row[c * 8], row[c * 8 + 1]};
                    const uint32_t* vv = reinterpret_cast<const uint32_t*>(vx);
                    uint32_t u[8];
#pragma unroll
                    for (int j = 0; j < 8; j++) u[j] = hmul2(pv[j], vv[j]);
                    row[c * 8] = make_uint4(__byte_perm(u[0], u[1], 0x5410), __byte_perm(u[2], u[3], 0x5410),
                                            __byte_perm(u[4], u[5], 0x5410), __byte_perm(u[6], u[7], 0x5410));
                    row[c * 8 + 1] = make_uint4(__byte_perm(u[0], u[1], 0x7632), __byte_perm(u[2], u[3], 0x7632),
                                                __byte_perm(u[4], u[5], 0x7632), __byte_perm(u[6], u[7], 0x7632));
                }
            }
            asm volatile("fence.proxy.async.shared::cta;" ::: "memory");
            __syncwarp();
            if (tid == 0) STAMP(3);
            if (lane == 0) {
                bulk_s2g(g_tab + (size_t)tile * 16 * ROWB, smem_u32(tb), nrows * 512);
                asm volatile("cp.async.bulk.commit_group;" ::: "memory");
                asm volatile("cp.async.bulk.wait_group 0;" ::: "memory");
            }
            if (tid == 0) STAMP(4);
        }
    } else {
        const int ptid = tid - 32 * P1_WARPS, pwarp = warp - P1_WARPS;
        const uint32_t bar = smem_u32(smem + PS_BAR);
        const int posbytes = N * 6;
        if (ptid == 0) {
            mbar_init(bar, 1);
            asm volatile("fence.mbarrier_init.release.cluster;" ::: "memory");
            mbar_expect_tx(bar, posbytes);
            bulk_g2s(smem_u32(smem + PS_POS), pos, posbytes, bar);
        }
        const int npairs = E >> 1;
        const int ppc = (npairs + NCTA - 1) / NCTA;
        const int pbeg = blockIdx.x * ppc, pend = min(pbeg + ppc, npairs);
        int2 es[P3_ITERS], ed[P3_ITERS];
#pragma unroll
        for (int it = 0; it < P3_ITERS; it++) {
            const int p = pbeg + ptid + it * P3_THREADS;
            if (p < pend) {
                es[it] = __ldcs(reinterpret_cast<const int2*>(src) + p);
                ed[it] = __ldcs(reinterpret_cast<const int2*>(dst) + p);
            }
        }
        int* hist = reinterpret_cast<int*>(smem + PS_HIST);
        for (int i = ptid; i < 1280; i += P3_THREADS) hist[i] = 0;
        {
            const int gi = ptid * NCTA + blockIdx.x;
            if (gi < NTAB * NRBF) {
                const int di = gi >> 4, k = gi & 15;
                const float d = __uint_as_float((uint32_t)(DBASE + di) << 16);
                const float arg = bf16r(d * __bfloat162float(freqs[k]));
                const float rbf = bf16r(bf16r(sinf(arg)) / d);
                const float ca = bf16r(bf16r(3.14159265358979f * d) / 5.0f);
                const float fc = 0.5f * bf16r(bf16r(cosf(ca)) + 1.0f);
                g_G[gi] = __float2bfloat16_rn(rbf * fc);
            }
        }
        if (ptid == 0) STAMP(5);
        asm volatile("bar.sync 2, %0;" ::"n"(P3_THREADS) : "memory");
        if (ptid == 0) STAMP(6);
        mbar_wait(bar, 0);
        if (ptid == 0) STAMP(7);
        const uint32_t* pw = reinterpret_cast<const uint32_t*>(smem + PS_POS);
        uint2 rec[P3_ITERS * 2];
        int key[P3_ITERS * 2];
#pragma unroll
        for (int q = 0; q < P3_ITERS * 2; q++) {
            const int it = q >> 1;
            key[q] = -1;
            if (pbeg + ptid + it * P3_THREADS < pend) {
                const int s = (q & 1) ? es[it].y : es[it].x;
                const int dd = (q & 1) ? ed[it].y : ed[it].x;
                const int ws = (s * 3) >> 1, wd = (dd * 3) >> 1;
                const uint32_t sa = pw[ws], sb = pw[ws + 1], da = pw[wd], db = pw[wd + 1];
                const uint32_t shs = (s & 1) << 4, shd = (dd & 1) << 4;
                const uint32_t rxy = hsub2(__funnelshift_r(sa, sb, shs), __funnelshift_r(da, db, shd));
                const uint32_t rz = hsub2(sb >> shs, db >> shd);
                const uint32_t qxy = hmul2(rxy, rxy), qz = hmul2(rz, rz);
                const float sum = (__uint_as_float(qxy << 16) + __uint_as_float(qxy & 0xffff0000u)) + __uint_as_float(qz << 16);
                if (sum < 23.9375f) {
                    const uint32_t exy = hmul2(rxy, 0x1e801e80u), ez = hmul2(rz, 0x1e801e80u);
                    rec[q].x = exy | ((dd & 3) << 13) | ((dd & 12) << 27);
                    rec[q].y = (ez & 0xffffu) | ((dd & 48) << 9) | ((uint32_t)s << 16) | ((uint32_t)(dd & 64) << 25);
                    const int grp = dd >> 3;
                    key[q] = (grp << 13) | atomicAdd(&hist[grp], 1);
                }
            }
        }
        if (ptid == 0) STAMP(8);
        asm volatile("bar.sync 2, %0;" ::"n"(P3_THREADS) : "memory");
        if (ptid == 0) STAMP(9);
        int2 hv = make_int2(0, 0);
        int incl = 0;
        if (pwarp < 20) {
            hv = reinterpret_cast<int2*>(hist)[ptid];
            incl = hv.x + hv.y;
#pragma unroll
            for (int o = 1; o < 32; o <<= 1) {
                const int v = __shfl_up_sync(0xffffffffu, incl, o);
                if (lane >= o) incl += v;
            }
            if (lane == 31) hist[1280 + pwarp] = incl;
        }
        asm volatile("bar.sync 2, %0;" ::"n"(P3_THREADS) : "memory");
        if (pwarp < 20) {
            int wsum = (lane < pwarp) ? hist[1280 + lane] : 0;
            wsum = __reduce_add_sync(0xffffffffu, wsum);
            const int ex = wsum + incl - hv.x - hv.y;
            reinterpret_cast<int2*>(hist)[ptid] = make_int2(ex, ex + hv.x);
        }
        asm volatile("bar.sync 2, %0;" ::"n"(P3_THREADS) : "memory");
        if (ptid == 0) STAMP(10);
        uint2* srec = reinterpret_cast<uint2*>(smem + PS_REC);
#pragma unroll
        for (int q = 0; q < P3_ITERS * 2; q++)
            if (key[q] >= 0) srec[hist[key[q] >> 13] + (key[q] & 8191)] = rec[q];
        const int ngroups = (N + GRP - 1) / GRP;
        unsigned short* spfx = reinterpret_cast<unsigned short*>(smem + PS_PFX);
        for (int i = ptid; i < NCTA * 16; i += P3_THREADS)
            spfx[i] = (unsigned short)hist[min(group_begin(i >> 4, ngroups) + (i & 15), ngroups)];
        asm volatile("fence.proxy.async.shared::cta;" ::: "memory");
        asm volatile("bar.sync 2, %0;" ::"n"(P3_THREADS) : "memory");
        if (ptid == 0) {
            STAMP(11);
            const int total = hist[ngroups];
            const int bytes = ((total + 1) >> 1) * 16;
            if (bytes > 0) bulk_s2g(g_rec + blockIdx.x * CH, smem_u32(srec), bytes);
            bulk_s2g(g_pfx + blockIdx.x * NCTA * 16, smem_u32(spfx), NCTA * 32);
            asm volatile("cp.async.bulk.commit_group;" ::: "memory");
            asm volatile("cp.async.bulk.wait_group 0;" ::: "memory");
            STAMP(12);
        }
    }
}

constexpr int UNITS = 3;
constexpr int STAGES = 3;
constexpr int M_THREADS = UNITS * 128 + 128;
constexpr int ST_G = 4 * 4096;
constexpr int ST_S = ST_G + 1024;
constexpr int ST_R = ST_S + 512;
constexpr int ST_CTL = ST_R + 192;
constexpr int STAGE_BYTES = ST_S + 1024;
constexpr int RCAP = 5888;
constexpr int MAXQ = 10;
constexpr int HOT0 = 0x3F00 - DBASE;
constexpr int MS_REC = UNITS * STAGES * STAGE_BYTES;
constexpr int MS_GH = MS_REC + RCAP * 8;
constexpr int MS_B2 = MS_GH + (NTAB - HOT0) * 32;
constexpr int MS_MISC = MS_B2 + MAXQ * 136 * 4;
constexpr int MS_BAR = MS_MISC + 32 * 4;
constexpr int M_SMEM = MS_BAR + 8;
static_assert(M_SMEM <= 232448, "smem");
static_assert(MS_BAR % 8 == 0 && MS_GH % 16 == 0 && STAGE_BYTES % 1024 == 0, "align");

template <int ACC, uint32_t HI>
__device__ __forceinline__ void wgmma_n32(float (&d)[16], const uint32_t (&a)[4], uint32_t lo) {
    if (ACC) {
        asm volatile("{\n.reg .b64 dd;\nmov.b64 dd, {%20, %21};\n"
                     "wgmma.mma_async.sync.aligned.m64n32k16.f32.bf16.bf16 {%0,%1,%2,%3,%4,%5,%6,%7,%8,%9,%10,%11,%12,%13,%14,%15}, {%16,%17,%18,%19}, dd, 1, 1, 1, 0;\n}\n"
                     : "+f"(d[0]), "+f"(d[1]), "+f"(d[2]), "+f"(d[3]), "+f"(d[4]), "+f"(d[5]), "+f"(d[6]), "+f"(d[7]),
                       "+f"(d[8]), "+f"(d[9]), "+f"(d[10]), "+f"(d[11]), "+f"(d[12]), "+f"(d[13]), "+f"(d[14]), "+f"(d[15])
                     : "r"(a[0]), "r"(a[1]), "r"(a[2]), "r"(a[3]), "r"(lo), "n"(HI));
    } else {
        asm volatile("{\n.reg .b64 dd;\nmov.b64 dd, {%20, %21};\n"
                     "wgmma.mma_async.sync.aligned.m64n32k16.f32.bf16.bf16 {%0,%1,%2,%3,%4,%5,%6,%7,%8,%9,%10,%11,%12,%13,%14,%15}, {%16,%17,%18,%19}, dd, 0, 1, 1, 0;\n}\n"
                     : "=f"(d[0]), "=f"(d[1]), "=f"(d[2]), "=f"(d[3]), "=f"(d[4]), "=f"(d[5]), "=f"(d[6]), "=f"(d[7]),
                       "=f"(d[8]), "=f"(d[9]), "=f"(d[10]), "=f"(d[11]), "=f"(d[12]), "=f"(d[13]), "=f"(d[14]), "=f"(d[15])
                     : "r"(a[0]), "r"(a[1]), "r"(a[2]), "r"(a[3]), "r"(lo), "n"(HI));
    }
}
constexpr uint32_t DESC_H = 64u | (1u << 30);
constexpr uint32_t DESC_G = 16u | (3u << 30);
__device__ __forceinline__ void reg_fence16(float (&d)[16]) {
    asm volatile("" : "+f"(d[0]), "+f"(d[1]), "+f"(d[2]), "+f"(d[3]), "+f"(d[4]), "+f"(d[5]), "+f"(d[6]), "+f"(d[7]),
                      "+f"(d[8]), "+f"(d[9]), "+f"(d[10]), "+f"(d[11]), "+f"(d[12]), "+f"(d[13]), "+f"(d[14]), "+f"(d[15]) :: "memory");
}
__device__ __forceinline__ uint32_t pin(uint32_t x) { return __shfl_sync(0xffffffffu, x, threadIdx.x & 31); }

template <bool FITS>
__device__ __forceinline__ void producer_loop(unsigned char* smem, const __nv_bfloat16* __restrict__ sv, int N,
                                              int unit, int q0, int nq) {
    const uint32_t sbase = smem_u32(smem);
    const uint32_t ubase = __reduce_or_sync(0xffffffffu, sbase + unit * STAGES * STAGE_BYTES);
    int* misc = reinterpret_cast<int*>(smem + MS_MISC);
    const int ln = pin(threadIdx.x & 31);
    const int r4 = ln >> 3;
    const unsigned char* gsrc = g_tab + (ln & 7) * 16;
    asm volatile("" : "+l"(gsrc));
    const uint32_t d0 = r4 * 128 + (((ln & 7) ^ r4) << 4);
    const uint32_t goff = ST_G + ln * 32 + (((ln >> 2) & 1) << 4);
    const uint32_t roff = ST_R + ((ln >> 1) & 3) * 16 + (ln >> 3) * 4 + (ln & 1) * 2;
    const unsigned char* ghot = smem + (MS_GH - HOT0 * 32);
    const unsigned char* gcold = reinterpret_cast<const unsigned char*>(g_G);
    asm volatile("" : "+l"(ghot), "+l"(gcold));
    uint32_t sb = ubase, ph = 1;
    int q = (int)__reduce_or_sync(0xffffffffu, (uint32_t)unit);
    while (q < nq) {
        int base = (ln < q) ? misc[ln] : 0;
        uint32_t ra = sbase + MS_REC + (__reduce_add_sync(0xffffffffu, base) + ln) * 8;
        const int cnt = (int)__reduce_or_sync(0xffffffffu, (uint32_t)misc[q]);
        int rem = cnt;
        const int grp = q0 + q;
        const unsigned char* svp = reinterpret_cast<const unsigned char*>(sv) + (size_t)(grp * GRP + r4) * 512 + (ln & 7) * 16;
        auto fetch = [&](int left) -> uint2 {
            uint2 r = make_uint2(0, 0);
            if (FITS) {
                asm volatile("ld.shared.v2.u32 {%0,%1}, [%2];" : "=r"(r.x), "=r"(r.y) : "r"(ra));
                ra += 256;
            } else if (ln < left) {
                const int j = cnt - left + ln;
                const int* prq = reinterpret_cast<const int*>(smem + MS_B2) + q * 136;
                int lo = 0, hi = NCTA;
                while (hi - lo > 1) {
                    const int mid = (lo + hi) >> 1;
                    if (prq[mid] <= j) lo = mid; else hi = mid;
                }
                r = __ldcg(g_rec + lo * CH + __ldcg(g_pfx + (lo * NCTA + blockIdx.x) * 16 + q) + (j - prq[lo]));
            }
            return r;
        };
        uint2 rn = fetch(rem);
        bool last;
        do {
            const bool valid = ln < rem;
            last = rem <= 24;
            const uint2 r = valid ? rn : make_uint2(0, 0);
            rn = fetch(rem - 32);
            const uint32_t srcv = (r.y >> 16) & 0x7fffu;
            const unsigned char* gq[8];
#pragma unroll
            for (int k = 0; k < 8; k++)
                gq[k] = gsrc + (size_t)__shfl_sync(0xffffffffu, srcv, k * 4 + r4) * ROWB;
            const int lim = rem - r4;
            const int lim6 = last ? N - grp * GRP + 24 - r4 : lim;
            if (last) { gq[6] = svp; gq[7] = svp + 4 * 512; }
            const uint32_t rxy = hmul2(r.x & 0x9fff9fffu, 0x60806080u);
            const uint32_t rz2 = hmul2(r.y & 0x00009fffu, 0x60806080u);
            const uint32_t qxy = hmul2(rxy, rxy), qz = hmul2(rz2, rz2);
            const float sum = bf16r((__uint_as_float(qxy << 16) + __uint_as_float(qxy & 0xffff0000u)) + __uint_as_float(qz << 16));
            float sq;
            asm("sqrt.approx.ftz.f32 %0, %1;" : "=f"(sq) : "f"(bf16r(sum + 1e-8f)));
            const uint32_t dbits = pack_bf16(0.f, sq);
            float rinv;
            asm("rcp.approx.ftz.f32 %0, %1;" : "=f"(rinv) : "f"(__uint_as_float(dbits)));
            const int di = valid ? max(min((int)(dbits >> 16), DEND - 1) - DBASE, 0) : NTAB - 1;
            const uint4* gp = reinterpret_cast<const uint4*>(di >= HOT0 ? ghot : gcold) + 2 * di;
            const uint4 g0 = gp[0], g1 = gp[1];
            const uint32_t r01 = pack_bf16(__uint_as_float(rxy << 16) * rinv, __uint_as_float(rxy & 0xffff0000u) * rinv);
            const uint32_t r2 = pack_bf16(__uint_as_float(rz2 << 16) * rinv, valid ? 1.0f : 0.f);
            const uint32_t so = ((r.x >> 12) & 6u) | ((r.x >> 26) & 8u);
            const uint32_t fl = ((uint32_t)grp << 4) | (last ? 2u : 0u);

            const uint32_t bar = sb + ST_CTL;
            mbar_wait(bar + 8, ph);
            const uint32_t dpa = sb + d0, dpb = (dpa ^ 64u) + 512u;
#pragma unroll
            for (int k = 0; k < 8; k++) {
                asm volatile("{\n.reg .pred p;\nsetp.le.s32 p, %2, %3;\n"
                             "cp.async.cg.shared.global [%0], [%1], 16, p;\n"
                             "cp.async.cg.shared.global [%0+4096], [%1+128], 16, p;\n"
                             "cp.async.cg.shared.global [%0+8192], [%1+256], 16, p;\n"
                             "cp.async.cg.shared.global [%0+12288], [%1+384], 16, p;\n}\n"
                             ::"r"(((k & 1) ? dpb : dpa) + (k >> 1) * 1024), "l"(gq[k]), "r"(k < 6 ? lim : lim6), "r"(4 * k) : "memory");
            }
            asm volatile("cp.async.mbarrier.arrive.noinc.shared::cta.b64 [%0];" ::"r"(bar) : "memory");
            const uint32_t za = sb + ST_S + ln * 16;
            asm volatile("st.shared.v4.u32 [%0], {%1,%1,%1,%1};" ::"r"(za), "r"(0u) : "memory");
            asm volatile("st.shared.u16 [%0], %1;" ::"r"(za + so), "h"((unsigned short)(r2 >> 16)) : "memory");
            asm volatile("st.shared.u16 [%0], %1;" ::"r"(sb + roff), "h"((unsigned short)(r01 & 0xffffu)) : "memory");
            asm volatile("st.shared.u16 [%0+64], %1;" ::"r"(sb + roff), "h"((unsigned short)(r01 >> 16)) : "memory");
            asm volatile("st.shared.u16 [%0+128], %1;" ::"r"(sb + roff), "h"((unsigned short)(r2 & 0xffffu)) : "memory");
            asm volatile("st.shared.u32 [%0+16], %1;" ::"r"(bar), "r"(fl) : "memory");
            asm volatile("st.shared.v4.u32 [%0], {%1,%2,%3,%4};" ::"r"(sb + goff),
                         "r"(g0.x), "r"(g0.y), "r"(g0.z), "r"(g0.w) : "memory");
            asm volatile("st.shared.v4.u32 [%0], {%1,%2,%3,%4};" ::"r"((sb + goff) ^ 16u),
                         "r"(g1.x), "r"(g1.y), "r"(g1.z), "r"(g1.w) : "memory");
            mbar_arrive(bar);
            sb += STAGE_BYTES;
            if (sb == ubase + STAGES * STAGE_BYTES) { sb = ubase; ph ^= 1; }
            rem -= 32;
        } while (!last);
        int nx = 0;
        if (ln == 0) nx = atomicAdd(&misc[16], 1);
        q = (int)__reduce_or_sync(0xffffffffu, (uint32_t)nx);
    }
    const uint32_t bar = sb + ST_CTL;
    mbar_wait(bar + 8, ph);
    asm volatile("st.shared.u32 [%0+16], %1;" ::"r"(bar), "r"(8u) : "memory");
    mbar_arrive(bar);
    mbar_arrive(bar);
}

__global__ void __launch_bounds__(M_THREADS, 1)
main_kernel(const __nv_bfloat16* __restrict__ sv, const __nv_bfloat16* __restrict__ w2,
            const __nv_bfloat16* __restrict__ wrbf, __nv_bfloat16* __restrict__ out, int N) {
    extern __shared__ __align__(1024) unsigned char smem[];
    const int tid = threadIdx.x, warp = tid >> 5, lane = tid & 31;
    const int g = lane >> 2, t = lane & 3;
    const int ngroups = (N + GRP - 1) / GRP;
    const int q0 = group_begin(blockIdx.x, ngroups);
    const int nq = group_begin(blockIdx.x + 1, ngroups) - q0;
    const uint32_t sbase = smem_u32(smem);
    const uint32_t ghbar = sbase + MS_BAR;
    int* misc = reinterpret_cast<int*>(smem + MS_MISC);
    const bool is_prod = warp >= UNITS * 4;

    if (tid == 0) {
        STAMP(16);
        for (int i = 0; i < UNITS * STAGES; i++) {
            mbar_init(sbase + i * STAGE_BYTES + ST_CTL, 64);
            mbar_init(sbase + i * STAGE_BYTES + ST_CTL + 8, 4);
        }
        mbar_init(ghbar, 1);
        asm volatile("fence.mbarrier_init.release.cluster;" ::: "memory");
        misc[16] = UNITS;
    }
    if (tid == 0) STAMP(17);
    asm volatile("griddepcontrol.wait;" ::: "memory");
    if (tid == 0) STAMP(18);

    const unsigned short* pfx = g_pfx + blockIdx.x * 16;
    int* b2 = reinterpret_cast<int*>(smem + MS_B2);
    uint2* srec = reinterpret_cast<uint2*>(smem + MS_REC);
    {
        if (tid == 0) {
            mbar_expect_tx(ghbar, (NTAB - HOT0) * 32);
            bulk_g2s(sbase + MS_GH, g_G + HOT0 * NRBF, (NTAB - HOT0) * 32, ghbar);
        }
        int beg = 0, end = 0;
        {
            const int p = warp + 16 * lane;
            if (p < NCTA) {
                beg = __ldcg(pfx + p * NCTA * 16);
                end = __ldcg(pfx + p * NCTA * 16 + nq);
            }
        }
        int lo[5], cq[5];
        if (warp < nq) {
#pragma unroll
            for (int k = 0; k < 5; k++) {
                const int p = lane * 5 + k;
                lo[k] = 0; cq[k] = 0;
                if (p < NCTA) {
                    lo[k] = __ldcg(pfx + p * NCTA * 16 + warp);
                    cq[k] = __ldcg(pfx + p * NCTA * 16 + warp + 1);
                }
            }
        }
        uint2 r[9];
#pragma unroll
        for (int k = 0; k < 9; k++) {
            const int i = __shfl_sync(0xffffffffu, beg, k) + lane;
            const int e = __shfl_sync(0xffffffffu, end, k);
            if (i < e) r[k] = __ldcg(g_rec + (warp + 16 * k) * CH + i);
        }
        int pre = 0;
        if (warp < nq) {
            int sum = 0;
#pragma unroll
            for (int k = 0; k < 5; k++) { cq[k] -= lo[k]; sum += cq[k]; }
            int in2 = sum;
#pragma unroll
            for (int o = 1; o < 32; o <<= 1) {
                const int v = __shfl_up_sync(0xffffffffu, in2, o);
                if (lane >= o) in2 += v;
            }
            pre = in2 - sum;
            if (lane == 31) misc[warp] = in2;
        }
        __syncthreads();
        if (tid == 0) STAMP(19);
        const int tv = lane < nq ? misc[lane] : 0;
        const bool fits = __reduce_add_sync(0xffffffffu, tv) <= RCAP;
        if (warp < nq) {
            if (fits) pre += __reduce_add_sync(0xffffffffu, lane < warp ? tv : 0);
#pragma unroll
            for (int k = 0; k < 5; k++) {
                const int p = lane * 5 + k;
                if (p < NCTA) b2[warp * 136 + p] = fits ? pre - lo[k] : pre;
                pre += cq[k];
            }
        }
        __syncthreads();
        if (fits) {
#pragma unroll
            for (int k = 0; k < 9; k++) {
                const int p = warp + 16 * k;
                int i = __shfl_sync(0xffffffffu, beg, k) + lane;
                const int e = __shfl_sync(0xffffffffu, end, k);
                uint2 v = r[k];
                while (i < e) {
                    const int q = (int)((((v.x >> 30) & 1u) | ((v.y >> 12) & 6u) | ((v.y >> 28) & 8u)) - (uint32_t)q0) & 15;
                    srec[b2[q * 136 + p] + i] = v;
                    i += 32;
                    if (i < e) v = __ldcg(g_rec + p * CH + i);
                }
            }
        }
        if (tid == 0) misc[17] = fits;
        __syncthreads();
    }
    if (tid == 0) STAMP(20);

    if (is_prod) {
        asm volatile("setmaxnreg.dec.sync.aligned.u32 80;");
        const int unit = warp - UNITS * 4;
        if (unit < UNITS) {
            mbar_wait(ghbar, 0);
            if (unit == 0 && lane == 0) STAMP(21);
            if (misc[17]) producer_loop<true>(smem, sv, N, unit, q0, nq);
            else producer_loop<false>(smem, sv, N, unit, q0, nq);
            if (lane == 0) STAMP(22 + unit);
        }
    } else {
        asm volatile("setmaxnreg.inc.sync.aligned.u32 144;");
        const int unit = warp >> 2, w = warp & 3;
        const uint32_t ubase = sbase + unit * STAGES * STAGE_BYTES;
        uint32_t wa[3][4], pa[2][4][4];
        {
            const int c = 16 * w + 2 * g;
#pragma unroll
            for (int p = 0; p < 3; p++)
#pragma unroll
                for (int kh = 0; kh < 2; kh++) {
                    const uint32_t lo = __ldg(reinterpret_cast<const uint32_t*>(wrbf + (2 * t + 8 * kh) * 192 + p * 64 + c));
                    const uint32_t hi = __ldg(reinterpret_cast<const uint32_t*>(wrbf + (2 * t + 8 * kh + 1) * 192 + p * 64 + c));
                    wa[p][2 * kh + 0] = __byte_perm(lo, hi, 0x5410);
                    wa[p][2 * kh + 1] = __byte_perm(lo, hi, 0x7632);
                }
#pragma unroll
            for (int p = 0; p < 2; p++)
#pragma unroll
                for (int q = 0; q < 4; q++)
#pragma unroll
                    for (int kh = 0; kh < 2; kh++) {
                        const int r = 8 * (t + 4 * kh) + 2 * q;
                        const uint32_t lo = __ldg(reinterpret_cast<const uint32_t*>(w2 + r * 192 + p * 128 + c));
                        const uint32_t hi = __ldg(reinterpret_cast<const uint32_t*>(w2 + (r + 1) * 192 + p * 128 + c));
                        pa[p][q][2 * kh + 0] = __byte_perm(lo, hi, 0x5410);
                        pa[p][q][2 * kh + 1] = __byte_perm(lo, hi, 0x7632);
                    }
        }
        float acc[4][4];
#pragma unroll
        for (int c = 0; c < 4; c++)
#pragma unroll
            for (int e = 0; e < 4; e++) acc[c][e] = 0.f;
        const int erow = (lane & 7) + 8 * (lane >> 4);
        const int ehalf = (lane >> 3) & 1;
        const uint32_t ua = pin(4096 + erow * 128 + ((uint32_t)((2 * w + ehalf) ^ (lane & 7)) << 4));
        const uint32_t sa = pin(ST_S + lane * 16);
        const uint32_t ra = pin(ST_R + t * 16);
        const uint32_t ub = __reduce_or_sync(0xffffffffu, ubase);
        uint32_t sb = ub;
        uint32_t ph = 0;
        const bool elected = sa == ST_S;
        while (true) {
            mbar_wait(sb + ST_CTL, ph);
            {
                asm volatile("fence.proxy.async.shared::cta;" ::: "memory");
                const uint32_t dh = (sb >> 4) | (1u << 16);
                const uint32_t dg = dh + (ST_G >> 4);
                uint32_t m[2][4], wv[2][4], u[3][4], sf[4], rr[3][2];
                float p0[16], f0[16], fv[16];
                asm volatile("wgmma.fence.sync.aligned;" ::: "memory");
                wgmma_n32<0, DESC_G>(f0, wa[2], dg);
                wgmma_n32<0, DESC_H>(p0, pa[1][0], dh);
                wgmma_n32<1, DESC_H>(p0, pa[1][1], dh + 2);
                wgmma_n32<1, DESC_H>(p0, pa[1][2], dh + 4);
                wgmma_n32<1, DESC_H>(p0, pa[1][3], dh + 6);
                wgmma_n32<0, DESC_G>(fv, wa[1], dg);
                asm volatile("wgmma.commit_group.sync.aligned;" ::: "memory");
#pragma unroll
                for (int j = 0; j < 3; j++) {
                    ldsm4t(u[j], sb + ua + j * 4096);
                    asm volatile("ld.shared.v2.u32 {%0,%1}, [%2];" : "=r"(rr[j][0]), "=r"(rr[j][1]) : "r"(sb + ra + j * 64));
                }
                ldsm4t(sf, sb + sa);
                asm volatile("wgmma.wait_group.sync.aligned 0;" ::: "memory");
                reg_fence16(fv); reg_fence16(f0); reg_fence16(p0);
#pragma unroll
                for (int i = 0; i < 8; i++) {
                    m[i >> 2][i & 3] = pack_bf16(f0[2 * i] * p0[2 * i], f0[2 * i + 1] * p0[2 * i + 1]);
                    wv[i >> 2][i & 3] = pack_bf16(fv[2 * i], fv[2 * i + 1]);
                }
                asm volatile("wgmma.fence.sync.aligned;" ::: "memory");
                wgmma_n32<0, DESC_G>(f0, wa[0], dg);
                wgmma_n32<0, DESC_H>(p0, pa[0][0], dh);
                wgmma_n32<1, DESC_H>(p0, pa[0][1], dh + 2);
                wgmma_n32<1, DESC_H>(p0, pa[0][2], dh + 4);
                wgmma_n32<1, DESC_H>(p0, pa[0][3], dh + 6);
                asm volatile("wgmma.commit_group.sync.aligned;" ::: "memory");
                uint32_t v1[3][4];
#pragma unroll
                for (int j = 0; j < 3; j++)
#pragma unroll
                    for (int e = 0; e < 4; e++) u[j][e] = hfma2(m[0][e], rr[j][e >> 1], hmul2(u[j][e], wv[0][e]));
#pragma unroll
                for (int j = 0; j < 3; j++) {
                    ldsm4t(v1[j], sb + ua + j * 4096 + 2048);
                    asm volatile("ld.shared.v2.u32 {%0,%1}, [%2];" : "=r"(rr[j][0]), "=r"(rr[j][1]) : "r"(sb + ra + j * 64 + 8));
                }
#pragma unroll
                for (int j = 0; j < 3; j++)
#pragma unroll
                    for (int e = 0; e < 4; e++) v1[j][e] = hfma2(m[1][e], rr[j][e >> 1], hmul2(v1[j][e], wv[1][e]));
#pragma unroll
                for (int j = 0; j < 3; j++) mma16816(acc[j + 1], u[j], sf[0], sf[1]);
#pragma unroll
                for (int j = 0; j < 3; j++) mma16816(acc[j + 1], v1[j], sf[2], sf[3]);
                asm volatile("wgmma.wait_group.sync.aligned 0;" ::: "memory");
                reg_fence16(f0); reg_fence16(p0);
#pragma unroll
                for (int i = 0; i < 8; i++)
                    m[i >> 2][i & 3] = pack_bf16(f0[2 * i] * p0[2 * i], f0[2 * i + 1] * p0[2 * i + 1]);
                mma16816(acc[0], m[0], sf[0], sf[1]);
                mma16816(acc[0], m[1], sf[2], sf[3]);
            }
            uint32_t flags;
            asm volatile("ld.shared.u32 %0, [%1+16];" : "=r"(flags) : "r"(sb + ST_CTL));
            if (flags & 10u) {
                if (flags & 8u) break;
                const int node0 = (int)(flags >> 4) * GRP + 2 * t;
                uint32_t* op = reinterpret_cast<uint32_t*>(out) + (size_t)node0 * 128 + 8 * w + g;
#pragma unroll
                for (int b = 0; b < 2; b++) {
                    const uint32_t va = sb + (24 + 2 * t + b) * 128 + (((uint32_t)(2 * w + (g >> 2)) ^ (uint32_t)(2 * t + b)) << 4) + (g & 3) * 4;
#pragma unroll
                    for (int c = 0; c < 4; c++) {
                        uint32_t v;
                        asm volatile("ld.shared.u32 %0, [%1];" : "=r"(v) : "r"(va + c * 4096));
                        const uint32_t o = pack_bf16(__uint_as_float(v << 16) + acc[c][b],
                                                     __uint_as_float(v & 0xffff0000u) + acc[c][2 + b]);
                        if (node0 + b < N) op[b * 128 + c * 32] = o;
                        acc[c][b] = 0.f; acc[c][2 + b] = 0.f;
                    }
                }
            }
            __syncwarp();
            if (elected) mbar_arrive(sb + ST_CTL + 8);
            sb += STAGE_BYTES;
            if (sb == ub + STAGES * STAGE_BYTES) { sb = ub; ph ^= 1; }
        }
        if (lane == 0 && w == 0) STAMP(26 + unit);
    }
}

}

extern "C" void kernel_launch(void* const* d_in, const int* in_sizes, int n_in, void* d_out, int out_size) {
    const __nv_bfloat16* sv = (const __nv_bfloat16*)d_in[0];
    const __nv_bfloat16* pos = (const __nv_bfloat16*)d_in[1];
    const int* src = (const int*)d_in[2];
    const int* dst = (const int*)d_in[3];
    const __nv_bfloat16* freqs = (const __nv_bfloat16*)d_in[4];
    const __nv_bfloat16* w1 = (const __nv_bfloat16*)d_in[5];
    const __nv_bfloat16* w2 = (const __nv_bfloat16*)d_in[6];
    const __nv_bfloat16* wrbf = (const __nv_bfloat16*)d_in[7];
    __nv_bfloat16* out = (__nv_bfloat16*)d_out;
    const int N = in_sizes[1] / 3;
    const int E = in_sizes[2];

    static bool init = false;
    if (!init) {
        cudaFuncSetAttribute(prep_kernel, cudaFuncAttributeMaxDynamicSharedMemorySize, PS_TOTAL);
        cudaFuncSetAttribute(main_kernel, cudaFuncAttributeMaxDynamicSharedMemorySize, M_SMEM);
        init = true;
    }
    cudaStream_t stream = cudaStreamPerThread;
    prep_kernel<<<NCTA, P_THREADS, PS_TOTAL, stream>>>(sv, pos, src, dst, freqs, w1, w2, N, E);

    cudaLaunchConfig_t cfg = {};
    cfg.gridDim = dim3(NCTA);
    cfg.blockDim = dim3(M_THREADS);
    cfg.dynamicSmemBytes = M_SMEM;
    cfg.stream = stream;
    cudaLaunchAttribute at[1];
    at[0].id = cudaLaunchAttributeProgrammaticStreamSerialization;
    at[0].val.programmaticStreamSerializationAllowed = 1;
    cfg.attrs = at;
    cfg.numAttrs = 1;
    cudaLaunchKernelEx(&cfg, main_kernel, sv, w2, wrbf, out, N);
}
```

```cpp
#include <cuda_runtime.h>
#include <cuda_bf16.h>
#include <stdint.h>

namespace {

constexpr int D = 64;
constexpr int NRBF = 16;
constexpr int MAXN = 10000;
constexpr int MAXE = 640000;
constexpr int NCTA = 132;
constexpr int GRP = 8;
constexpr int NPC = (MAXN + NCTA - 1) / NCTA;
constexpr int NQ = (NPC + GRP - 1) / GRP;
constexpr int NBIN = NCTA * NQ;
constexpr int CH = 4864;
constexpr int DBASE = 0x38C0;
constexpr int DEND = 0x40A0;
constexpr int NTAB = DEND - DBASE;
constexpr int ROWB = 512;

__device__ __align__(128) unsigned char g_tab[(size_t)(MAXN + 16) * ROWB];
__device__ __align__(128) __nv_bfloat16 g_G[NTAB * NRBF];
__device__ __align__(128) uint2 g_rec[NCTA * CH];
__device__ __align__(128) unsigned short g_pfx[NCTA * NCTA * 16];

#define STAMP(k) do {} while (0)

__device__ __forceinline__ uint32_t smem_u32(const void* p) { return (uint32_t)__cvta_generic_to_shared(p); }
__device__ __forceinline__ uint32_t pack_bf16(float lo, float hi) {
    uint32_t r;
    asm("cvt.rn.bf16x2.f32 %0, %1, %2;" : "=r"(r) : "f"(hi), "f"(lo));
    return r;
}
__device__ __forceinline__ float bf16r(float x) { return __uint_as_float(pack_bf16(0.f, x) & 0xffff0000u); }
__device__ __forceinline__ uint32_t hmul2(uint32_t a, uint32_t b) {
    uint32_t r;
    asm("mul.rn.bf16x2 %0, %1, %2;" : "=r"(r) : "r"(a), "r"(b));
    return r;
}
__device__ __forceinline__ uint32_t hsub2(uint32_t a, uint32_t b) {
    uint32_t r;
    asm("sub.rn.bf16x2 %0, %1, %2;" : "=r"(r) : "r"(a), "r"(b));
    return r;
}
__device__ __forceinline__ uint32_t hfma2(uint32_t a, uint32_t b, uint32_t c) {
    uint32_t r;
    asm("fma.rn.bf16x2 %0, %1, %2, %3;" : "=r"(r) : "r"(a), "r"(b), "r"(c));
    return r;
}
__device__ __forceinline__ void mma16816(float (&c)[4], const uint32_t (&a)[4], uint32_t b0, uint32_t b1) {
    asm volatile("mma.sync.aligned.m16n8k16.row.col.f32.bf16.bf16.f32 {%0,%1,%2,%3}, {%4,%5,%6,%7}, {%8,%9}, {%0,%1,%2,%3};"
                 : "+f"(c[0]), "+f"(c[1]), "+f"(c[2]), "+f"(c[3])
                 : "r"(a[0]), "r"(a[1]), "r"(a[2]), "r"(a[3]), "r"(b0), "r"(b1));
}
__device__ __forceinline__ void mma16816_z(float (&c)[4], const uint32_t (&a)[4], uint32_t b0, uint32_t b1) {
    asm volatile("mma.sync.aligned.m16n8k16.row.col.f32.bf16.bf16.f32 {%0,%1,%2,%3}, {%4,%5,%6,%7}, {%8,%9}, {%10,%10,%10,%10};"
                 : "=f"(c[0]), "=f"(c[1]), "=f"(c[2]), "=f"(c[3])
                 : "r"(a[0]), "r"(a[1]), "r"(a[2]), "r"(a[3]), "r"(b0), "r"(b1), "f"(0.f));
}
__device__ __forceinline__ void ldsm4(uint32_t (&r)[4], uint32_t addr) {
    asm volatile("ldmatrix.sync.aligned.m8n8.x4.shared.b16 {%0,%1,%2,%3}, [%4];"
                 : "=r"(r[0]), "=r"(r[1]), "=r"(r[2]), "=r"(r[3]) : "r"(addr));
}
__device__ __forceinline__ void ldsm4t(uint32_t (&r)[4], uint32_t addr) {
    asm volatile("ldmatrix.sync.aligned.m8n8.x4.trans.shared.b16 {%0,%1,%2,%3}, [%4];"
                 : "=r"(r[0]), "=r"(r[1]), "=r"(r[2]), "=r"(r[3]) : "r"(addr));
}
__device__ __forceinline__ void mbar_init(uint32_t bar, int cnt) {
    asm volatile("mbarrier.init.shared::cta.b64 [%0], %1;" ::"r"(bar), "r"(cnt) : "memory");
}
__device__ __forceinline__ void mbar_arrive(uint32_t bar) {
    asm volatile("mbarrier.arrive.shared::cta.b64 _, [%0];" ::"r"(bar) : "memory");
}
__device__ __forceinline__ void mbar_expect_tx(uint32_t bar, uint32_t bytes) {
    asm volatile("mbarrier.arrive.expect_tx.shared::cta.b64 _, [%0], %1;" ::"r"(bar), "r"(bytes) : "memory");
}
__device__ __forceinline__ void mbar_wait(uint32_t bar, uint32_t parity) {
    asm volatile(
        "{\n.reg .pred p;\n.reg .u32 n;\nmov.u32 n, 0;\n"
        "WAIT_%=:\n"
        "mbarrier.try_wait.parity.shared::cta.b64 p, [%0], %1, %2;\n"
        "@p bra DONE_%=;\n"
        "add.u32 n, n, 1;\n"
        "setp.lt.u32 p, n, 100000;\n"
        "@p bra WAIT_%=;\n"
        "exit;\n"
        "DONE_%=:\n}\n" ::"r"(bar), "r"(parity), "r"(10000u) : "memory");
}
__device__ __forceinline__ void bulk_g2s(uint32_t dst, const void* src, uint32_t bytes, uint32_t bar) {
    asm volatile("cp.async.bulk.shared::cluster.global.mbarrier::complete_tx::bytes [%0], [%1], %2, [%3];"
                 ::"r"(dst), "l"(src), "r"(bytes), "r"(bar) : "memory");
}
__device__ __forceinline__ void bulk_s2g(void* dst, uint32_t src, uint32_t bytes) {
    asm volatile("cp.async.bulk.global.shared::cta.bulk_group [%0], [%1], %2;" ::"l"(dst), "r"(src), "r"(bytes) : "memory");
}

constexpr int P_THREADS = 1024;
constexpr int P1_WARPS = 5;
constexpr int P3_THREADS = P_THREADS - 32 * P1_WARPS;
constexpr int P3_ITERS = 3;
constexpr int W_PITCH = 144;
constexpr int PS_TILE = 0;
constexpr int PS_REC = PS_TILE + P1_WARPS * 8192;
constexpr int PS_PFX = PS_REC + CH * 8;
constexpr int PS_POS = PS_PFX + NCTA * 32;
constexpr int PS_W1 = PS_POS + 60032;
constexpr int PS_W2 = PS_W1 + 64 * W_PITCH;
constexpr int PS_HIST = PS_W2 + 64 * W_PITCH;
constexpr int PS_BAR = PS_HIST + (1344 + 32) * 4;
constexpr int PS_TOTAL = PS_BAR + 64;

__global__ void __launch_bounds__(P_THREADS, 1)
prep_kernel(const __nv_bfloat16* __restrict__ sv, const __nv_bfloat16* __restrict__ pos,
            const int* __restrict__ src, const int* __restrict__ dst,
            const __nv_bfloat16* __restrict__ freqs, const __nv_bfloat16* __restrict__ w1,
            const __nv_bfloat16* __restrict__ w2, int N, int E) {
    extern __shared__ __align__(1024) unsigned char smem[];
    const int tid = threadIdx.x, warp = tid >> 5, lane = tid & 31;
    asm volatile("griddepcontrol.launch_dependents;");
    if (tid == 0) STAMP(0);

    if (warp < P1_WARPS) {
        const int g = lane >> 2, t = lane & 3;
        const int tile = warp * gridDim.x + blockIdx.x;
        const int nrows = min(16, N - tile * 16);
        const uint32_t bar = smem_u32(smem + PS_BAR + 8 + 8 * warp);
        unsigned char* tb = smem + PS_TILE + warp * 8192;
        if (nrows > 0 && lane == 0) {
            mbar_init(bar, 1);
            asm volatile("fence.mbarrier_init.release.cluster;" ::: "memory");
            mbar_expect_tx(bar, nrows * 512);
            bulk_g2s(smem_u32(tb), sv + (size_t)tile * 16 * 256, nrows * 512, bar);
        }
        for (int i = tid; i < 64 * 8; i += 32 * P1_WARPS) {
            const int r = i >> 3, c = i & 7;
            *reinterpret_cast<uint4*>(smem + PS_W1 + r * W_PITCH + c * 16) =
                __ldg(reinterpret_cast<const uint4*>(w1 + r * 64) + c);
            const uint4 v = __ldg(reinterpret_cast<const uint4*>(w2 + r * 192 + 64) + c);
            const int tt = c >> 1, j0 = (c & 1) * 4;
            uint32_t* o = reinterpret_cast<uint32_t*>(smem + PS_W2 + r * W_PITCH);
            o[4 * (j0 + 0) + tt] = v.x; o[4 * (j0 + 1) + tt] = v.y;
            o[4 * (j0 + 2) + tt] = v.z; o[4 * (j0 + 3) + tt] = v.w;
        }
        asm volatile("bar.sync 1, %0;" ::"n"(32 * P1_WARPS) : "memory");
        if (tid == 0) STAMP(1);
        if (nrows > 0) {
            mbar_wait(bar, 0);
            if (tid == 0) STAMP(2);
            uint4* r0 = reinterpret_cast<uint4*>(tb + g * 512 + t * 32);
            uint4* r1 = reinterpret_cast<uint4*>(tb + (g + 8) * 512 + t * 32);
            uint32_t h[4][4];
            {
                uint4 xa[2] = {r0[0], r0[1]}, xb[2] = {r1[0], r1[1]};
                const uint32_t* s0 = reinterpret_cast<const uint32_t*>(xa);
                const uint32_t* s1 = reinterpret_cast<const uint32_t*>(xb);
                float a[8][4];
                const int i = lane & 7, hi = (lane >> 3) & 1, nsel = lane >> 4;
#pragma unroll
                for (int q = 0; q < 4; q++) {
                    const int krow = 16 * (i >> 1) + 4 * q + (i & 1) + 2 * hi;
                    const uint32_t af[4] = {s0[2 * q], s1[2 * q], s0[2 * q + 1], s1[2 * q + 1]};
#pragma unroll
                    for (int jp = 0; jp < 4; jp++) {
                        uint32_t b[4];
                        ldsm4t(b, smem_u32(smem + PS_W1 + krow * W_PITCH + (2 * jp + nsel) * 16));
                        if (q == 0) {
                            mma16816_z(a[2 * jp], af, b[0], b[1]);
                            mma16816_z(a[2 * jp + 1], af, b[2], b[3]);
                        } else {
                            mma16816(a[2 * jp], af, b[0], b[1]);
                            mma16816(a[2 * jp + 1], af, b[2], b[3]);
                        }
                    }
                }
#pragma unroll
                for (int j = 0; j < 8; j++) {
                    float f[4];
#pragma unroll
                    for (int e = 0; e < 4; e++) {
                        const float z = bf16r(a[j][e]);
                        f[e] = __fdividef(z, 1.0f + __expf(-z));
                    }
                    h[j >> 1][(j & 1) * 2 + 0] = pack_bf16(f[0], f[1]);
                    h[j >> 1][(j & 1) * 2 + 1] = pack_bf16(f[2], f[3]);
                }
            }
            r0[0] = make_uint4(h[0][0], h[0][2], h[1][0], h[1][2]);
            r0[1] = make_uint4(h[2][0], h[2][2], h[3][0], h[3][2]);
            r1[0] = make_uint4(h[0][1], h[0][3], h[1][1], h[1][3]);
            r1[1] = make_uint4(h[2][1], h[2][3], h[3][1], h[3][3]);
            float p[8][4];
            {
                const int i = lane & 15, nsel = lane >> 4;
#pragma unroll
                for (int q = 0; q < 4; q++) {
#pragma unroll
                    for (int jp = 0; jp < 4; jp++) {
                        uint32_t b[4];
                        ldsm4t(b, smem_u32(smem + PS_W2 + (16 * q + i) * W_PITCH + (2 * jp + nsel) * 16));
                        if (q == 0) {
                            mma16816_z(p[2 * jp], h[0], b[0], b[1]);
                            mma16816_z(p[2 * jp + 1], h[0], b[2], b[3]);
                        } else {
                            mma16816(p[2 * jp], h[q], b[0], b[1]);
                            mma16816(p[2 * jp + 1], h[q], b[2], b[3]);
                        }
                    }
                }
            }
#pragma unroll
            for (int r = 0; r < 2; r++) {
                uint4* row = r ? r1 : r0;
                uint32_t pv[8];
#pragma unroll
                for (int j = 0; j < 8; j++) pv[j] = pack_bf16(p[j][2 * r], p[j][2 * r + 1]);
#pragma unroll
                for (int c = 1; c < 4; c++) {
                    uint4 vx[2] = {row[c * 8], row[c * 8 + 1]};
                    const uint32_t* vv = reinterpret_cast<const uint32_t*>(vx);
                    uint32_t u[8];
#pragma unroll
                    for (int j = 0; j < 8; j++) u[j] = hmul2(pv[j], vv[j]);
                    row[c * 8] = make_uint4(__byte_perm(u[0], u[1], 0x5410), __byte_perm(u[2], u[3], 0x5410),
                                            __byte_perm(u[4], u[5], 0x5410), __byte_perm(u[6], u[7], 0x5410));
                    row[c * 8 + 1] = make_uint4(__byte_perm(u[0], u[1], 0x7632), __byte_perm(u[2], u[3], 0x7632),
                                                __byte_perm(u[4], u[5], 0x7632), __byte_perm(u[6], u[7], 0x7632));
                }
            }
            asm volatile("fence.proxy.async.shared::cta;" ::: "memory");
            __syncwarp();
            if (tid == 0) STAMP(3);
            if (lane == 0) {
                bulk_s2g(g_tab + (size_t)tile * 16 * ROWB, smem_u32(tb), nrows * 512);
                asm volatile("cp.async.bulk.commit_group;" ::: "memory");
                asm volatile("cp.async.bulk.wait_group 0;" ::: "memory");
            }
            if (tid == 0) STAMP(4);
        }
    } else {
        const int ptid = tid - 32 * P1_WARPS, pwarp = warp - P1_WARPS;
        const uint32_t bar = smem_u32(smem + PS_BAR);
        const int posbytes = N * 6;
        if (ptid == 0) {
            mbar_init(bar, 1);
            asm volatile("fence.mbarrier_init.release.cluster;" ::: "memory");
            mbar_expect_tx(bar, posbytes);
            bulk_g2s(smem_u32(smem + PS_POS), pos, posbytes, bar);
        }
        const int npairs = E >> 1;
        const int ppc = (npairs + NCTA - 1) / NCTA;
        const int pbeg = blockIdx.x * ppc, pend = min(pbeg + ppc, npairs);
        int2 es[P3_ITERS], ed[P3_ITERS];
#pragma unroll
        for (int it = 0; it < P3_ITERS; it++) {
            const int p = pbeg + ptid + it * P3_THREADS;
            if (p < pend) {
                es[it] = __ldcs(reinterpret_cast<const int2*>(src) + p);
                ed[it] = __ldcs(reinterpret_cast<const int2*>(dst) + p);
            }
        }
        int* hist = reinterpret_cast<int*>(smem + PS_HIST);
        for (int i = ptid; i < 1344; i += P3_THREADS) hist[i] = 0;
        {
            const int gi = ptid * NCTA + blockIdx.x;
            if (gi < NTAB * NRBF) {
                const int di = gi >> 4, k = gi & 15;
                const float d = __uint_as_float((uint32_t)(DBASE + di) << 16);
                const float arg = bf16r(d * __bfloat162float(freqs[k]));
                const float rbf = bf16r(bf16r(sinf(arg)) / d);
                const float ca = bf16r(bf16r(3.14159265358979f * d) / 5.0f);
                const float fc = 0.5f * bf16r(bf16r(cosf(ca)) + 1.0f);
                g_G[gi] = __float2bfloat16_rn(rbf * fc);
            }
        }
        if (ptid == 0) STAMP(5);
        asm volatile("bar.sync 2, %0;" ::"n"(P3_THREADS) : "memory");
        if (ptid == 0) STAMP(6);
        mbar_wait(bar, 0);
        if (ptid == 0) STAMP(7);
        const uint32_t* pw = reinterpret_cast<const uint32_t*>(smem + PS_POS);
        uint2 rec[P3_ITERS * 2];
        int key[P3_ITERS * 2];
#pragma unroll
        for (int q = 0; q < P3_ITERS * 2; q++) {
            const int it = q >> 1;
            key[q] = -1;
            if (pbeg + ptid + it * P3_THREADS < pend) {
                const int s = (q & 1) ? es[it].y : es[it].x;
                const int dd = (q & 1) ? ed[it].y : ed[it].x;
                const int ws = (s * 3) >> 1, wd = (dd * 3) >> 1;
                const uint32_t sa = pw[ws], sb = pw[ws + 1], da = pw[wd], db = pw[wd + 1];
                const uint32_t shs = (s & 1) << 4, shd = (dd & 1) << 4;
                const uint32_t rxy = hsub2(__funnelshift_r(sa, sb, shs), __funnelshift_r(da, db, shd));
                const uint32_t rz = hsub2(sb >> shs, db >> shd);
                const uint32_t qxy = hmul2(rxy, rxy), qz = hmul2(rz, rz);
                const float sum = (__uint_as_float(qxy << 16) + __uint_as_float(qxy & 0xffff0000u)) + __uint_as_float(qz << 16);
                if (sum < 23.9375f) {
                    const uint32_t exy = hmul2(rxy, 0x1e801e80u), ez = hmul2(rz, 0x1e801e80u);
                    const int c = dd / NPC, dl = dd - c * NPC;
                    rec[q].x = exy | ((dl & 3) << 13) | ((dl & 12) << 27);
                    rec[q].y = (ez & 0xffffu) | ((dl & 48) << 9) | ((uint32_t)s << 16) | ((uint32_t)(dl & 64) << 25);
                    const int grp = c * NQ + (dl >> 3);
                    key[q] = (grp << 13) | atomicAdd(&hist[grp], 1);
                }
            }
        }
        if (ptid == 0) STAMP(8);
        asm volatile("bar.sync 2, %0;" ::"n"(P3_THREADS) : "memory");
        if (ptid == 0) STAMP(9);
        int2 hv = make_int2(0, 0);
        int incl = 0;
        if (pwarp < 21) {
            hv = reinterpret_cast<int2*>(hist)[ptid];
            incl = hv.x + hv.y;
#pragma unroll
            for (int o = 1; o < 32; o <<= 1) {
                const int v = __shfl_up_sync(0xffffffffu, incl, o);
                if (lane >= o) incl += v;
            }
            if (lane == 31) hist[1344 + pwarp] = incl;
        }
        asm volatile("bar.sync 2, %0;" ::"n"(P3_THREADS) : "memory");
        if (pwarp < 21) {
            int wsum = (lane < pwarp) ? hist[1344 + lane] : 0;
            wsum = __reduce_add_sync(0xffffffffu, wsum);
            const int ex = wsum + incl - hv.x - hv.y;
            reinterpret_cast<int2*>(hist)[ptid] = make_int2(ex, ex + hv.x);
        }
        asm volatile("bar.sync 2, %0;" ::"n"(P3_THREADS) : "memory");
        if (ptid == 0) STAMP(10);
        uint2* srec = reinterpret_cast<uint2*>(smem + PS_REC);
#pragma unroll
        for (int q = 0; q < P3_ITERS * 2; q++)
            if (key[q] >= 0) srec[hist[key[q] >> 13] + (key[q] & 8191)] = rec[q];
        unsigned short* spfx = reinterpret_cast<unsigned short*>(smem + PS_PFX);
        for (int i = ptid; i < NCTA * 16; i += P3_THREADS)
            spfx[i] = (unsigned short)hist[(i >> 4) * NQ + (i & 15)];
        asm volatile("fence.proxy.async.shared::cta;" ::: "memory");
        asm volatile("bar.sync 2, %0;" ::"n"(P3_THREADS) : "memory");
        if (ptid == 0) {
            STAMP(11);
            const int total = hist[NBIN];
            const int bytes = ((total + 1) >> 1) * 16;
            if (bytes > 0) bulk_s2g(g_rec + blockIdx.x * CH, smem_u32(srec), bytes);
            bulk_s2g(g_pfx + blockIdx.x * NCTA * 16, smem_u32(spfx), NCTA * 32);
            asm volatile("cp.async.bulk.commit_group;" ::: "memory");
            asm volatile("cp.async.bulk.wait_group 0;" ::: "memory");
            STAMP(12);
        }
    }
}

constexpr int UNITS = 3;
constexpr int STAGES = 3;
constexpr int M_THREADS = UNITS * 128 + 128;
constexpr int ST_G = 4 * 4096;
constexpr int ST_S = ST_G + 1024;
constexpr int ST_R = ST_S + 512;
constexpr int ST_CTL = ST_R + 192;
constexpr int STAGE_BYTES = ST_S + 1024;
constexpr int RCAP = 3904;
constexpr int HOT0 = 0x3F00 - DBASE;
constexpr int MS_REC = UNITS * STAGES * STAGE_BYTES;
constexpr int MS_PART = MS_REC + RCAP * 8;
constexpr int MS_GH = MS_PART + 2 * 8192;
constexpr int MS_B2 = MS_GH + (NTAB - HOT0) * 32;
constexpr int MS_MISC = MS_B2 + NQ * 136 * 4;
constexpr int MS_BAR = MS_MISC + 32 * 4;
constexpr int M_SMEM = MS_BAR + 24;
static_assert(M_SMEM <= 232448, "smem");
static_assert(MS_BAR % 8 == 0 && MS_GH % 16 == 0 && STAGE_BYTES % 1024 == 0, "align");

template <int ACC, uint32_t HI>
__device__ __forceinline__ void wgmma_n32(float (&d)[16], const uint32_t (&a)[4], uint32_t lo) {
    if (ACC) {
        asm volatile("{\n.reg .b64 dd;\nmov.b64 dd, {%20, %21};\n"
                     "wgmma.mma_async.sync.aligned.m64n32k16.f32.bf16.bf16 {%0,%1,%2,%3,%4,%5,%6,%7,%8,%9,%10,%11,%12,%13,%14,%15}, {%16,%17,%18,%19}, dd, 1, 1, 1, 0;\n}\n"
                     : "+f"(d[0]), "+f"(d[1]), "+f"(d[2]), "+f"(d[3]), "+f"(d[4]), "+f"(d[5]), "+f"(d[6]), "+f"(d[7]),
                       "+f"(d[8]), "+f"(d[9]), "+f"(d[10]), "+f"(d[11]), "+f"(d[12]), "+f"(d[13]), "+f"(d[14]), "+f"(d[15])
                     : "r"(a[0]), "r"(a[1]), "r"(a[2]), "r"(a[3]), "r"(lo), "n"(HI));
    } else {
        asm volatile("{\n.reg .b64 dd;\nmov.b64 dd, {%20, %21};\n"
                     "wgmma.mma_async.sync.aligned.m64n32k16.f32.bf16.bf16 {%0,%1,%2,%3,%4,%5,%6,%7,%8,%9,%10,%11,%12,%13,%14,%15}, {%16,%17,%18,%19}, dd, 0, 1, 1, 0;\n}\n"
                     : "=f"(d[0]), "=f"(d[1]), "=f"(d[2]), "=f"(d[3]), "=f"(d[4]), "=f"(d[5]), "=f"(d[6]), "=f"(d[7]),
                       "=f"(d[8]), "=f"(d[9]), "=f"(d[10]), "=f"(d[11]), "=f"(d[12]), "=f"(d[13]), "=f"(d[14]), "=f"(d[15])
                     : "r"(a[0]), "r"(a[1]), "r"(a[2]), "r"(a[3]), "r"(lo), "n"(HI));
    }
}
constexpr uint32_t DESC_H = 64u | (1u << 30);
constexpr uint32_t DESC_G = 16u | (3u << 30);
__device__ __forceinline__ void reg_fence16(float (&d)[16]) {
    asm volatile("" : "+f"(d[0]), "+f"(d[1]), "+f"(d[2]), "+f"(d[3]), "+f"(d[4]), "+f"(d[5]), "+f"(d[6]), "+f"(d[7]),
                      "+f"(d[8]), "+f"(d[9]), "+f"(d[10]), "+f"(d[11]), "+f"(d[12]), "+f"(d[13]), "+f"(d[14]), "+f"(d[15]) :: "memory");
}
__device__ __forceinline__ uint32_t pin(uint32_t x) { return __shfl_sync(0xffffffffu, x, threadIdx.x & 31); }

template <bool FITS>
__device__ __forceinline__ void producer_loop(unsigned char* smem, const __nv_bfloat16* __restrict__ sv, int N, int unit) {
    const uint32_t sbase = smem_u32(smem);
    const uint32_t ubase = __reduce_or_sync(0xffffffffu, sbase + unit * STAGES * STAGE_BYTES);
    const int* misc = reinterpret_cast<const int*>(smem + MS_MISC);
    const int ln = pin(threadIdx.x & 31);
    const int r4 = ln >> 3;
    const unsigned char* gsrc = g_tab + (ln & 7) * 16;
    asm volatile("" : "+l"(gsrc));
    const uint32_t d0 = r4 * 128 + (((ln & 7) ^ r4) << 4);
    const uint32_t goff = ST_G + ln * 32 + (((ln >> 2) & 1) << 4);
    const uint32_t roff = ST_R + ((ln >> 1) & 3) * 16 + (ln >> 3) * 4 + (ln & 1) * 2;
    const unsigned char* ghot = smem + (MS_GH - HOT0 * 32);
    const unsigned char* gcold = reinterpret_cast<const unsigned char*>(g_G);
    asm volatile("" : "+l"(ghot), "+l"(gcold));
    uint32_t sb = ubase, ph = 1;
    const int tv = ln < NQ ? misc[ln] : 0;
    const int total = __reduce_add_sync(0xffffffffu, tv);
    const int s1 = total / 3, s2 = (2 * total) / 3;
    const int un = (int)__reduce_or_sync(0xffffffffu, (uint32_t)unit);
    const int ulo = un == 0 ? 0 : (un == 1 ? s1 : s2);
    const int uhi = un == 0 ? s1 : (un == 1 ? s2 : total);
    const int nnodes = min(NPC, N - (int)blockIdx.x * NPC);
    int gb = 0;
    for (int q = 0; q < NQ; q++) {
        const int gcnt = __reduce_add_sync(0xffffffffu, ln == q ? tv : 0);
        const int ge = gb + gcnt;
        const int beg = gb;
        gb = ge;
        const bool own = beg >= ulo && (beg < uhi || un == 2);
        const int lo = max(beg, ulo), hi = min(ge, uhi);
        if (!own && lo >= hi) continue;
        uint32_t ra = sbase + MS_REC + (lo + ln) * 8;
        const int cnt = hi - beg;
        int rem = max(hi - lo, 0);
        const int lastcap = own ? 24 : 32;
        uint32_t flast = own ? 2u : 4u;
        if (own && un == 0 && beg < s1 && s1 < ge && s1 < s2) flast |= 16u;
        if (own && un < 2 && beg < s2 && s2 < ge) flast |= 32u;
        const unsigned char* svp = reinterpret_cast<const unsigned char*>(sv) +
                                   (size_t)(blockIdx.x * NPC + q * GRP + r4) * 512 + (ln & 7) * 16;
        auto fetch = [&](int left) -> uint2 {
            uint2 r = make_uint2(0, 0);
            if (FITS) {
                asm volatile("ld.shared.v2.u32 {%0,%1}, [%2];" : "=r"(r.x), "=r"(r.y) : "r"(ra));
                ra += 256;
            } else if (ln < left) {
                const int j = cnt - left + ln;
                const int* prq = reinterpret_cast<const int*>(smem + MS_B2) + q * 136;
                int lo = 0, hi = NCTA;
                while (hi - lo > 1) {
                    const int mid = (lo + hi) >> 1;
                    if (prq[mid] <= j) lo = mid; else hi = mid;
                }
                r = __ldcg(g_rec + lo * CH + __ldcg(g_pfx + (lo * NCTA + blockIdx.x) * 16 + q) + (j - prq[lo]));
            }
            return r;
        };
        uint2 rn = fetch(rem);
        bool last;
        do {
            const bool valid = ln < rem;
            last = rem <= lastcap;
            const bool svl = last && own;
            const uint2 r = valid ? rn : make_uint2(0, 0);
            rn = fetch(rem - 32);
            const uint32_t srcv = (r.y >> 16) & 0x7fffu;
            const unsigned char* gq[8];
#pragma unroll
            for (int k = 0; k < 8; k++)
                gq[k] = gsrc + (size_t)__shfl_sync(0xffffffffu, srcv, k * 4 + r4) * ROWB;
            const int lim = rem - r4;
            const int lim6 = svl ? nnodes - q * GRP + 24 - r4 : lim;
            if (svl) { gq[6] = svp; gq[7] = svp + 4 * 512; }
            const uint32_t rxy = hmul2(r.x & 0x9fff9fffu, 0x60806080u);
            const uint32_t rz2 = hmul2(r.y & 0x00009fffu, 0x60806080u);
            const uint32_t qxy = hmul2(rxy, rxy), qz = hmul2(rz2, rz2);
            const float sum = bf16r((__uint_as_float(qxy << 16) + __uint_as_float(qxy & 0xffff0000u)) + __uint_as_float(qz << 16));
            float sq;
            asm("sqrt.approx.ftz.f32 %0, %1;" : "=f"(sq) : "f"(bf16r(sum + 1e-8f)));
            const uint32_t dbits = pack_bf16(0.f, sq);
            float rinv;
            asm("rcp.approx.ftz.f32 %0, %1;" : "=f"(rinv) : "f"(__uint_as_float(dbits)));
            const int di = valid ? max(min((int)(dbits >> 16), DEND - 1) - DBASE, 0) : NTAB - 1;
            const uint4* gp = reinterpret_cast<const uint4*>(di >= HOT0 ? ghot : gcold) + 2 * di;
            const uint4 g0 = gp[0], g1 = gp[1];
            const uint32_t r01 = pack_bf16(__uint_as_float(rxy << 16) * rinv, __uint_as_float(rxy & 0xffff0000u) * rinv);
            const uint32_t r2 = pack_bf16(__uint_as_float(rz2 << 16) * rinv, valid ? 1.0f : 0.f);
            const uint32_t so = ((r.x >> 12) & 6u) | ((r.x >> 26) & 8u);
            const uint32_t fl = last ? (((uint32_t)q << 8) | flast) : 0u;

            const uint32_t bar = sb + ST_CTL;
            mbar_wait(bar + 8, ph);
            const uint32_t dpa = sb + d0, dpb = (dpa ^ 64u) + 512u;
#pragma unroll
            for (int k = 0; k < 8; k++) {
                asm volatile("{\n.reg .pred p;\nsetp.le.s32 p, %2, %3;\n"
                             "cp.async.cg.shared.global [%0], [%1], 16, p;\n"
                             "cp.async.cg.shared.global [%0+4096], [%1+128], 16, p;\n"
                             "cp.async.cg.shared.global [%0+8192], [%1+256], 16, p;\n"
                             "cp.async.cg.shared.global [%0+12288], [%1+384], 16, p;\n}\n"
                             ::"r"(((k & 1) ? dpb : dpa) + (k >> 1) * 1024), "l"(gq[k]), "r"(k < 6 ? lim : lim6), "r"(4 * k) : "memory");
            }
            asm volatile("cp.async.mbarrier.arrive.noinc.shared::cta.b64 [%0];" ::"r"(bar) : "memory");
            const uint32_t za = sb + ST_S + ln * 16;
            asm volatile("st.shared.v4.u32 [%0], {%1,%1,%1,%1};" ::"r"(za), "r"(0u) : "memory");
            asm volatile("st.shared.u16 [%0], %1;" ::"r"(za + so), "h"((unsigned short)(r2 >> 16)) : "memory");
            asm volatile("st.shared.u16 [%0], %1;" ::"r"(sb + roff), "h"((unsigned short)(r01 & 0xffffu)) : "memory");
            asm volatile("st.shared.u16 [%0+64], %1;" ::"r"(sb + roff), "h"((unsigned short)(r01 >> 16)) : "memory");
            asm volatile("st.shared.u16 [%0+128], %1;" ::"r"(sb + roff), "h"((unsigned short)(r2 & 0xffffu)) : "memory");
            asm volatile("st.shared.u32 [%0+16], %1;" ::"r"(bar), "r"(fl) : "memory");
            asm volatile("st.shared.v4.u32 [%0], {%1,%2,%3,%4};" ::"r"(sb + goff),
                         "r"(g0.x), "r"(g0.y), "r"(g0.z), "r"(g0.w) : "memory");
            asm volatile("st.shared.v4.u32 [%0], {%1,%2,%3,%4};" ::"r"((sb + goff) ^ 16u),
                         "r"(g1.x), "r"(g1.y), "r"(g1.z), "r"(g1.w) : "memory");
            asm volatile("fence.proxy.async.shared::cta;" ::: "memory");
            mbar_arrive(bar);
            sb += STAGE_BYTES;
            if (sb == ubase + STAGES * STAGE_BYTES) { sb = ubase; ph ^= 1; }
            rem -= 32;
        } while (!last);
    }
    const uint32_t bar = sb + ST_CTL;
    mbar_wait(bar + 8, ph);
    asm volatile("st.shared.u32 [%0+16], %1;" ::"r"(bar), "r"(8u) : "memory");
    mbar_arrive(bar);
    mbar_arrive(bar);
}

__global__ void __launch_bounds__(M_THREADS, 1)
main_kernel(const __nv_bfloat16* __restrict__ sv, const __nv_bfloat16* __restrict__ w2,
            const __nv_bfloat16* __restrict__ wrbf, __nv_bfloat16* __restrict__ out, int N) {
    extern __shared__ __align__(1024) unsigned char smem[];
    const int tid = threadIdx.x, warp = tid >> 5, lane = tid & 31;
    const int g = lane >> 2, t = lane & 3;
    constexpr int nq = NQ;
    const uint32_t sbase = smem_u32(smem);
    const uint32_t ghbar = sbase + MS_BAR;
    int* misc = reinterpret_cast<int*>(smem + MS_MISC);
    const bool is_prod = warp >= UNITS * 4;

    if (tid == 0) {
        STAMP(16);
        for (int i = 0; i < UNITS * STAGES; i++) {
            mbar_init(sbase + i * STAGE_BYTES + ST_CTL, 64);
            mbar_init(sbase + i * STAGE_BYTES + ST_CTL + 8, 4);
        }
        mbar_init(ghbar, 1);
        mbar_init(ghbar + 8, 128);
        mbar_init(ghbar + 16, 128);
        asm volatile("fence.mbarrier_init.release.cluster;" ::: "memory");
    }
    if (tid == 0) STAMP(17);
    asm volatile("griddepcontrol.wait;" ::: "memory");
    if (tid == 0) STAMP(18);

    const unsigned short* pfx = g_pfx + blockIdx.x * 16;
    int* b2 = reinterpret_cast<int*>(smem + MS_B2);
    uint2* srec = reinterpret_cast<uint2*>(smem + MS_REC);
    {
        if (tid == 0) {
            mbar_expect_tx(ghbar, (NTAB - HOT0) * 32);
            bulk_g2s(sbase + MS_GH, g_G + HOT0 * NRBF, (NTAB - HOT0) * 32, ghbar);
        }
        int beg = 0, end = 0;
        {
            const int p = warp + 16 * lane;
            if (p < NCTA) {
                beg = __ldcg(pfx + p * NCTA * 16);
                end = __ldcg(pfx + p * NCTA * 16 + nq);
            }
        }
        int lo[5], cq[5];
        if (warp < nq) {
#pragma unroll
            for (int k = 0; k < 5; k++) {
                const int p = lane * 5 + k;
                lo[k] = 0; cq[k] = 0;
                if (p < NCTA) {
                    lo[k] = __ldcg(pfx + p * NCTA * 16 + warp);
                    cq[k] = __ldcg(pfx + p * NCTA * 16 + warp + 1);
                }
            }
        }
        uint2 r[9];
#pragma unroll
        for (int k = 0; k < 9; k++) {
            const int i = __shfl_sync(0xffffffffu, beg, k) + lane;
            const int e = __shfl_sync(0xffffffffu, end, k);
            if (i < e) r[k] = __ldcg(g_rec + (warp + 16 * k) * CH + i);
        }
        int pre = 0;
        if (warp < nq) {
            int sum = 0;
#pragma unroll
            for (int k = 0; k < 5; k++) { cq[k] -= lo[k]; sum += cq[k]; }
            int in2 = sum;
#pragma unroll
            for (int o = 1; o < 32; o <<= 1) {
                const int v = __shfl_up_sync(0xffffffffu, in2, o);
                if (lane >= o) in2 += v;
            }
            pre = in2 - sum;
            if (lane == 31) misc[warp] = in2;
        }
        __syncthreads();
        if (tid == 0) STAMP(19);
        const int tv = lane < nq ? misc[lane] : 0;
        const bool fits = __reduce_add_sync(0xffffffffu, tv) <= RCAP;
        if (warp < nq) {
            if (fits) pre += __reduce_add_sync(0xffffffffu, lane < warp ? tv : 0);
#pragma unroll
            for (int k = 0; k < 5; k++) {
                const int p = lane * 5 + k;
                if (p < NCTA) b2[warp * 136 + p] = fits ? pre - lo[k] : pre;
                pre += cq[k];
            }
        }
        __syncthreads();
        if (fits) {
#pragma unroll
            for (int k = 0; k < 9; k++) {
                const int p = warp + 16 * k;
                int i = __shfl_sync(0xffffffffu, beg, k) + lane;
                const int e = __shfl_sync(0xffffffffu, end, k);
                uint2 v = r[k];
                while (i < e) {
                    const int q = (int)(((v.x >> 30) & 1u) | ((v.y >> 12) & 6u) | ((v.y >> 28) & 8u));
                    srec[b2[q * 136 + p] + i] = v;
                    i += 32;
                    if (i < e) v = __ldcg(g_rec + p * CH + i);
                }
            }
        }
        if (tid == 0) misc[17] = fits;
        __syncthreads();
    }
    if (tid == 0) STAMP(20);

    if (is_prod) {
        asm volatile("setmaxnreg.dec.sync.aligned.u32 80;");
        const int unit = warp - UNITS * 4;
        if (unit < UNITS) {
            mbar_wait(ghbar, 0);
            if (unit == 0 && lane == 0) STAMP(21);
            if (misc[17]) producer_loop<true>(smem, sv, N, unit);
            else producer_loop<false>(smem, sv, N, unit);
            if (lane == 0) STAMP(22 + unit);
        }
    } else {
        asm volatile("setmaxnreg.inc.sync.aligned.u32 144;");
        const int unit = warp >> 2, w = warp & 3;
        const uint32_t ubase = sbase + unit * STAGES * STAGE_BYTES;
        uint32_t wa[3][4], pa[2][4][4];
        {
            const int c = 16 * w + 2 * g;
#pragma unroll
            for (int p = 0; p < 3; p++)
#pragma unroll
                for (int kh = 0; kh < 2; kh++) {
                    const uint32_t lo = __ldg(reinterpret_cast<const uint32_t*>(wrbf + (2 * t + 8 * kh) * 192 + p * 64 + c));
                    const uint32_t hi = __ldg(reinterpret_cast<const uint32_t*>(wrbf + (2 * t + 8 * kh + 1) * 192 + p * 64 + c));
                    wa[p][2 * kh + 0] = __byte_perm(lo, hi, 0x5410);
                    wa[p][2 * kh + 1] = __byte_perm(lo, hi, 0x7632);
                }
#pragma unroll
            for (int p = 0; p < 2; p++)
#pragma unroll
                for (int q = 0; q < 4; q++)
#pragma unroll
                    for (int kh = 0; kh < 2; kh++) {
                        const int r = 8 * (t + 4 * kh) + 2 * q;
                        const uint32_t lo = __ldg(reinterpret_cast<const uint32_t*>(w2 + r * 192 + p * 128 + c));
                        const uint32_t hi = __ldg(reinterpret_cast<const uint32_t*>(w2 + (r + 1) * 192 + p * 128 + c));
                        pa[p][q][2 * kh + 0] = __byte_perm(lo, hi, 0x5410);
                        pa[p][q][2 * kh + 1] = __byte_perm(lo, hi, 0x7632);
                    }
        }
        float acc[4][4];
#pragma unroll
        for (int c = 0; c < 4; c++)
#pragma unroll
            for (int e = 0; e < 4; e++) acc[c][e] = 0.f;
        const int erow = (lane & 7) + 8 * (lane >> 4);
        const int ehalf = (lane >> 3) & 1;
        const uint32_t ua = pin(4096 + erow * 128 + ((uint32_t)((2 * w + ehalf) ^ (lane & 7)) << 4));
        const uint32_t sa = pin(ST_S + lane * 16);
        const uint32_t ra = pin(ST_R + t * 16);
        const uint32_t ub = __reduce_or_sync(0xffffffffu, ubase);
        uint32_t sb = ub;
        uint32_t ph = 0;
        const bool elected = sa == ST_S;
        while (true) {
            mbar_wait(sb + ST_CTL, ph);
            {
                const uint32_t dh = (sb >> 4) | (1u << 16);
                const uint32_t dg = dh + (ST_G >> 4);
                uint32_t m[2][4], wv[2][4], u[3][4], sf[4], rr[3][2];
                float p0[16], f0[16], fv[16];
                asm volatile("wgmma.fence.sync.aligned;" ::: "memory");
                wgmma_n32<0, DESC_G>(f0, wa[2], dg);
                wgmma_n32<0, DESC_H>(p0, pa[1][0], dh);
                wgmma_n32<1, DESC_H>(p0, pa[1][1], dh + 2);
                wgmma_n32<1, DESC_H>(p0, pa[1][2], dh + 4);
                wgmma_n32<1, DESC_H>(p0, pa[1][3], dh + 6);
                wgmma_n32<0, DESC_G>(fv, wa[1], dg);
                asm volatile("wgmma.commit_group.sync.aligned;" ::: "memory");
#pragma unroll
                for (int j = 0; j < 3; j++) {
                    ldsm4t(u[j], sb + ua + j * 4096);
                    asm volatile("ld.shared.v2.u32 {%0,%1}, [%2];" : "=r"(rr[j][0]), "=r"(rr[j][1]) : "r"(sb + ra + j * 64));
                }
                ldsm4t(sf, sb + sa);
                asm volatile("wgmma.wait_group.sync.aligned 0;" ::: "memory");
                reg_fence16(fv); reg_fence16(f0); reg_fence16(p0);
#pragma unroll
                for (int i = 0; i < 8; i++) {
                    m[i >> 2][i & 3] = pack_bf16(f0[2 * i] * p0[2 * i], f0[2 * i + 1] * p0[2 * i + 1]);
                    wv[i >> 2][i & 3] = pack_bf16(fv[2 * i], fv[2 * i + 1]);
                }
                asm volatile("wgmma.fence.sync.aligned;" ::: "memory");
                wgmma_n32<0, DESC_G>(f0, wa[0], dg);
                wgmma_n32<0, DESC_H>(p0, pa[0][0], dh);
                wgmma_n32<1, DESC_H>(p0, pa[0][1], dh + 2);
                wgmma_n32<1, DESC_H>(p0, pa[0][2], dh + 4);
                wgmma_n32<1, DESC_H>(p0, pa[0][3], dh + 6);
                asm volatile("wgmma.commit_group.sync.aligned;" ::: "memory");
                uint32_t v1[3][4];
#pragma unroll
                for (int j = 0; j < 3; j++)
#pragma unroll
                    for (int e = 0; e < 4; e++) u[j][e] = hfma2(m[0][e], rr[j][e >> 1], hmul2(u[j][e], wv[0][e]));
#pragma unroll
                for (int j = 0; j < 3; j++) {
                    ldsm4t(v1[j], sb + ua + j * 4096 + 2048);
                    asm volatile("ld.shared.v2.u32 {%0,%1}, [%2];" : "=r"(rr[j][0]), "=r"(rr[j][1]) : "r"(sb + ra + j * 64 + 8));
                }
#pragma unroll
                for (int j = 0; j < 3; j++)
#pragma unroll
                    for (int e = 0; e < 4; e++) v1[j][e] = hfma2(m[1][e], rr[j][e >> 1], hmul2(v1[j][e], wv[1][e]));
#pragma unroll
                for (int j = 0; j < 3; j++) mma16816(acc[j + 1], u[j], sf[0], sf[1]);
#pragma unroll
                for (int j = 0; j < 3; j++) mma16816(acc[j + 1], v1[j], sf[2], sf[3]);
                asm volatile("wgmma.wait_group.sync.aligned 0;" ::: "memory");
                reg_fence16(f0); reg_fence16(p0);
#pragma unroll
                for (int i = 0; i < 8; i++)
                    m[i >> 2][i & 3] = pack_bf16(f0[2 * i] * p0[2 * i], f0[2 * i + 1] * p0[2 * i + 1]);
                mma16816(acc[0], m[0], sf[0], sf[1]);
                mma16816(acc[0], m[1], sf[2], sf[3]);
            }
            uint32_t flags;
            asm volatile("ld.shared.u32 %0, [%1+16];" : "=r"(flags) : "r"(sb + ST_CTL));
            if (flags) {
                if (flags & 8u) break;
                float* part = reinterpret_cast<float*>(smem + MS_PART) + (tid & 127);
                if (flags & 4u) {
#pragma unroll
                    for (int i = 0; i < 16; i++) part[(unit - 1) * 2048 + i * 128] = acc[i >> 2][i & 3];
                    mbar_arrive(sbase + MS_BAR + unit * 8);
                } else {
#pragma unroll 1
                    for (int k = 0; k < 2; k++) {
                        if (flags & (16u << k)) {
                            mbar_wait(sbase + MS_BAR + 8 + k * 8, 0);
#pragma unroll
                            for (int i = 0; i < 16; i++) acc[i >> 2][i & 3] += part[k * 2048 + i * 128];
                        }
                    }
                    const int ln0 = (int)(flags >> 8) * GRP + 2 * t;
                    const int node0 = blockIdx.x * NPC + ln0;
                    uint32_t* op = reinterpret_cast<uint32_t*>(out) + (size_t)node0 * 128 + 8 * w + g;
#pragma unroll
                    for (int b = 0; b < 2; b++) {
                        const uint32_t va = sb + (24 + 2 * t + b) * 128 + (((uint32_t)(2 * w + (g >> 2)) ^ (uint32_t)(2 * t + b)) << 4) + (g & 3) * 4;
#pragma unroll
                        for (int c = 0; c < 4; c++) {
                            uint32_t v;
                            asm volatile("ld.shared.u32 %0, [%1];" : "=r"(v) : "r"(va + c * 4096));
                            const uint32_t o = pack_bf16(__uint_as_float(v << 16) + acc[c][b],
                                                         __uint_as_float(v & 0xffff0000u) + acc[c][2 + b]);
                            if (ln0 + b < NPC && node0 + b < N) op[b * 128 + c * 32] = o;
                        }
                    }
                }
#pragma unroll
                for (int i = 0; i < 16; i++) acc[i >> 2][i & 3] = 0.f;
            }
            __syncwarp();
            if (elected) mbar_arrive(sb + ST_CTL + 8);
            sb += STAGE_BYTES;
            if (sb == ub + STAGES * STAGE_BYTES) { sb = ub; ph ^= 1; }
        }
        if (lane == 0 && w == 0) STAMP(26 + unit);
    }
}

}

extern "C" void kernel_launch(void* const* d_in, const int* in_sizes, int n_in, void* d_out, int out_size) {
    const __nv_bfloat16* sv = (const __nv_bfloat16*)d_in[0];
    const __nv_bfloat16* pos = (const __nv_bfloat16*)d_in[1];
    const int* src = (const int*)d_in[2];
    const int* dst = (const int*)d_in[3];
    const __nv_bfloat16* freqs = (const __nv_bfloat16*)d_in[4];
    const __nv_bfloat16* w1 = (const __nv_bfloat16*)d_in[5];
    const __nv_bfloat16* w2 = (const __nv_bfloat16*)d_in[6];
    const __nv_bfloat16* wrbf = (const __nv_bfloat16*)d_in[7];
    __nv_bfloat16* out = (__nv_bfloat16*)d_out;
    const int N = in_sizes[1] / 3;
    const int E = in_sizes[2];

    static bool init = false;
    if (!init) {
        cudaFuncSetAttribute(prep_kernel, cudaFuncAttributeMaxDynamicSharedMemorySize, PS_TOTAL);
        cudaFuncSetAttribute(main_kernel, cudaFuncAttributeMaxDynamicSharedMemorySize, M_SMEM);
        init = true;
    }
    cudaStream_t stream = cudaStreamPerThread;
    prep_kernel<<<NCTA, P_THREADS, PS_TOTAL, stream>>>(sv, pos, src, dst, freqs, w1, w2, N, E);

    cudaLaunchConfig_t cfg = {};
    cfg.gridDim = dim3(NCTA);
    cfg.blockDim = dim3(M_THREADS);
    cfg.dynamicSmemBytes = M_SMEM;
    cfg.stream = stream;
    cudaLaunchAttribute at[1];
    at[0].id = cudaLaunchAttributeProgrammaticStreamSerialization;
    at[0].val.programmaticStreamSerializationAllowed = 1;
    cfg.attrs = at;
    cfg.numAttrs = 1;
    cudaLaunchKernelEx(&cfg, main_kernel, sv, w2, wrbf, out, N);
}
```

```cpp
#include <cuda_runtime.h>
#include <cuda_bf16.h>
#include <stdint.h>

namespace {

constexpr int D = 64;
constexpr int NRBF = 16;
constexpr int MAXN = 10000;
constexpr int MAXE = 640000;
constexpr int NCTA = 132;
constexpr int GRP = 8;
constexpr int NPC = (MAXN + NCTA - 1) / NCTA;
constexpr int NQ = (NPC + GRP - 1) / GRP;
constexpr int NBIN = NCTA * NQ;
constexpr int CH = 4864;
constexpr int DBASE = 0x38C0;
constexpr int DEND = 0x40A0;
constexpr int NTAB = DEND - DBASE;
constexpr int ROWB = 512;

__device__ __align__(128) unsigned char g_tab[(size_t)(MAXN + 16) * ROWB];
__device__ __align__(128) __nv_bfloat16 g_G[NTAB * NRBF];
__device__ __align__(128) uint2 g_rec[NCTA * CH];
__device__ __align__(128) uint4 g_pfx[NCTA * NCTA * 2];
__device__ unsigned int g_cnt;

#define STAMP(k, tt) do {} while (0)

__device__ __forceinline__ uint32_t smem_u32(const void* p) { return (uint32_t)__cvta_generic_to_shared(p); }
__device__ __forceinline__ uint32_t pack_bf16(float lo, float hi) {
    uint32_t r;
    asm("cvt.rn.bf16x2.f32 %0, %1, %2;" : "=r"(r) : "f"(hi), "f"(lo));
    return r;
}
__device__ __forceinline__ float bf16r(float x) { return __uint_as_float(pack_bf16(0.f, x) & 0xffff0000u); }
__device__ __forceinline__ uint32_t hmul2(uint32_t a, uint32_t b) {
    uint32_t r;
    asm("mul.rn.bf16x2 %0, %1, %2;" : "=r"(r) : "r"(a), "r"(b));
    return r;
}
__device__ __forceinline__ uint32_t hsub2(uint32_t a, uint32_t b) {
    uint32_t r;
    asm("sub.rn.bf16x2 %0, %1, %2;" : "=r"(r) : "r"(a), "r"(b));
    return r;
}
__device__ __forceinline__ uint32_t hfma2(uint32_t a, uint32_t b, uint32_t c) {
    uint32_t r;
    asm("fma.rn.bf16x2 %0, %1, %2, %3;" : "=r"(r) : "r"(a), "r"(b), "r"(c));
    return r;
}
__device__ __forceinline__ void mma16816(float (&c)[4], const uint32_t (&a)[4], uint32_t b0, uint32_t b1) {
    asm volatile("mma.sync.aligned.m16n8k16.row.col.f32.bf16.bf16.f32 {%0,%1,%2,%3}, {%4,%5,%6,%7}, {%8,%9}, {%0,%1,%2,%3};"
                 : "+f"(c[0]), "+f"(c[1]), "+f"(c[2]), "+f"(c[3])
                 : "r"(a[0]), "r"(a[1]), "r"(a[2]), "r"(a[3]), "r"(b0), "r"(b1));
}
__device__ __forceinline__ void mma16816_z(float (&c)[4], const uint32_t (&a)[4], uint32_t b0, uint32_t b1) {
    asm volatile("mma.sync.aligned.m16n8k16.row.col.f32.bf16.bf16.f32 {%0,%1,%2,%3}, {%4,%5,%6,%7}, {%8,%9}, {%10,%10,%10,%10};"
                 : "=f"(c[0]), "=f"(c[1]), "=f"(c[2]), "=f"(c[3])
                 : "r"(a[0]), "r"(a[1]), "r"(a[2]), "r"(a[3]), "r"(b0), "r"(b1), "f"(0.f));
}
__device__ __forceinline__ void ldsm4(uint32_t (&r)[4], uint32_t addr) {
    asm volatile("ldmatrix.sync.aligned.m8n8.x4.shared.b16 {%0,%1,%2,%3}, [%4];"
                 : "=r"(r[0]), "=r"(r[1]), "=r"(r[2]), "=r"(r[3]) : "r"(addr));
}
__device__ __forceinline__ void ldsm4t(uint32_t (&r)[4], uint32_t addr) {
    asm volatile("ldmatrix.sync.aligned.m8n8.x4.trans.shared.b16 {%0,%1,%2,%3}, [%4];"
                 : "=r"(r[0]), "=r"(r[1]), "=r"(r[2]), "=r"(r[3]) : "r"(addr));
}
__device__ __forceinline__ void stsm4t(uint32_t addr, const uint32_t (&r)[4]) {
    asm volatile("stmatrix.sync.aligned.m8n8.x4.trans.shared.b16 [%0], {%1,%2,%3,%4};"
                 ::"r"(addr), "r"(r[0]), "r"(r[1]), "r"(r[2]), "r"(r[3]) : "memory");
}
__device__ __forceinline__ void cp_async16(uint32_t dst, const void* src) {
    asm volatile("cp.async.cg.shared.global [%0], [%1], 16;" ::"r"(dst), "l"(src) : "memory");
}
__device__ __forceinline__ void mbar_init(uint32_t bar, int cnt) {
    asm volatile("mbarrier.init.shared::cta.b64 [%0], %1;" ::"r"(bar), "r"(cnt) : "memory");
}
__device__ __forceinline__ void mbar_arrive(uint32_t bar) {
    asm volatile("mbarrier.arrive.shared::cta.b64 _, [%0];" ::"r"(bar) : "memory");
}
__device__ __forceinline__ void mbar_expect_tx(uint32_t bar, uint32_t bytes) {
    asm volatile("mbarrier.arrive.expect_tx.shared::cta.b64 _, [%0], %1;" ::"r"(bar), "r"(bytes) : "memory");
}
__device__ __forceinline__ void mbar_wait(uint32_t bar, uint32_t parity) {
    asm volatile(
        "{\n.reg .pred p;\n.reg .u32 n;\nmov.u32 n, 0;\n"
        "WAIT_%=:\n"
        "mbarrier.try_wait.parity.shared::cta.b64 p, [%0], %1, %2;\n"
        "@p bra DONE_%=;\n"
        "add.u32 n, n, 1;\n"
        "setp.lt.u32 p, n, 100000;\n"
        "@p bra WAIT_%=;\n"
        "exit;\n"
        "DONE_%=:\n}\n" ::"r"(bar), "r"(parity), "r"(10000u) : "memory");
}
__device__ __forceinline__ void bulk_g2s(uint32_t dst, const void* src, uint32_t bytes, uint32_t bar) {
    asm volatile("cp.async.bulk.shared::cluster.global.mbarrier::complete_tx::bytes [%0], [%1], %2, [%3];"
                 ::"r"(dst), "l"(src), "r"(bytes), "r"(bar) : "memory");
}
__device__ __forceinline__ void bulk_s2g(void* dst, uint32_t src, uint32_t bytes) {
    asm volatile("cp.async.bulk.global.shared::cta.bulk_group [%0], [%1], %2;" ::"l"(dst), "r"(src), "r"(bytes) : "memory");
}

constexpr int UNITS = 3;
constexpr int STAGES = 3;
constexpr int M_THREADS = UNITS * 128 + 128;
constexpr int ST_G = 4 * 4096;
constexpr int ST_S = ST_G + 1024;
constexpr int ST_R = ST_S + 512;
constexpr int ST_CTL = ST_R + 192;
constexpr int STAGE_BYTES = ST_S + 1024;
constexpr int RCAP = 3904;
constexpr int HOT0 = 0x3F00 - DBASE;
constexpr int MS_REC = UNITS * STAGES * STAGE_BYTES;
constexpr int MS_PART = MS_REC + RCAP * 8;
constexpr int MS_GH = MS_PART + 2 * 8192;
constexpr int MS_B2 = MS_GH + (NTAB - HOT0) * 32;
constexpr int MS_MISC = MS_B2 + NQ * 136 * 4;
constexpr int MS_BAR = MS_MISC + 32 * 4;
constexpr int M_SMEM = MS_BAR + 64;
constexpr int EPC = 4852;
constexpr int PS_POS = UNITS * STAGE_BYTES;
constexpr int PS_SRC = PS_POS + 60032;
constexpr int PS_DST = PS_SRC + CH * 4;
constexpr int PS_KEY = PS_DST + CH * 4;
constexpr int PS_W1 = PS_KEY + CH * 4;
constexpr int PS_WV = PS_W1 + 64 * 144;
constexpr int PS_W2 = MS_PART;
constexpr int PS_WR = PS_W2 + 64 * 272;
constexpr int PS_HIST = PS_WR + 16 * 400;
constexpr int PS_PF = 8 * STAGE_BYTES;
static_assert(PS_WV + 64 * 144 <= MS_PART && PS_HIST + (1536 + 32) * 4 <= MS_MISC && EPC * NCTA >= MAXE && EPC <= CH && CH * 8 <= 60032, "phase-1 layout");
static_assert(M_SMEM <= 232448, "smem");
static_assert(MS_BAR % 8 == 0 && MS_GH % 16 == 0 && STAGE_BYTES % 1024 == 0, "align");

template <int ACC, uint32_t HI>
__device__ __forceinline__ void wgmma_n32(float (&d)[16], const uint32_t (&a)[4], uint32_t lo) {
    if (ACC) {
        asm volatile("{\n.reg .b64 dd;\nmov.b64 dd, {%20, %21};\n"
                     "wgmma.mma_async.sync.aligned.m64n32k16.f32.bf16.bf16 {%0,%1,%2,%3,%4,%5,%6,%7,%8,%9,%10,%11,%12,%13,%14,%15}, {%16,%17,%18,%19}, dd, 1, 1, 1, 0;\n}\n"
                     : "+f"(d[0]), "+f"(d[1]), "+f"(d[2]), "+f"(d[3]), "+f"(d[4]), "+f"(d[5]), "+f"(d[6]), "+f"(d[7]),
                       "+f"(d[8]), "+f"(d[9]), "+f"(d[10]), "+f"(d[11]), "+f"(d[12]), "+f"(d[13]), "+f"(d[14]), "+f"(d[15])
                     : "r"(a[0]), "r"(a[1]), "r"(a[2]), "r"(a[3]), "r"(lo), "n"(HI));
    } else {
        asm volatile("{\n.reg .b64 dd;\nmov.b64 dd, {%20, %21};\n"
                     "wgmma.mma_async.sync.aligned.m64n32k16.f32.bf16.bf16 {%0,%1,%2,%3,%4,%5,%6,%7,%8,%9,%10,%11,%12,%13,%14,%15}, {%16,%17,%18,%19}, dd, 0, 1, 1, 0;\n}\n"
                     : "=f"(d[0]), "=f"(d[1]), "=f"(d[2]), "=f"(d[3]), "=f"(d[4]), "=f"(d[5]), "=f"(d[6]), "=f"(d[7]),
                       "=f"(d[8]), "=f"(d[9]), "=f"(d[10]), "=f"(d[11]), "=f"(d[12]), "=f"(d[13]), "=f"(d[14]), "=f"(d[15])
                     : "r"(a[0]), "r"(a[1]), "r"(a[2]), "r"(a[3]), "r"(lo), "n"(HI));
    }
}
constexpr uint32_t DESC_H = 64u | (1u << 30);
constexpr uint32_t DESC_G = 16u | (3u << 30);
__device__ __forceinline__ void reg_fence16(float (&d)[16]) {
    asm volatile("" : "+f"(d[0]), "+f"(d[1]), "+f"(d[2]), "+f"(d[3]), "+f"(d[4]), "+f"(d[5]), "+f"(d[6]), "+f"(d[7]),
                      "+f"(d[8]), "+f"(d[9]), "+f"(d[10]), "+f"(d[11]), "+f"(d[12]), "+f"(d[13]), "+f"(d[14]), "+f"(d[15]) :: "memory");
}
__device__ __forceinline__ uint32_t pin(uint32_t x) { return __shfl_sync(0xffffffffu, x, threadIdx.x & 31); }

template <bool FITS>
__device__ __forceinline__ void producer_loop(unsigned char* smem, const __nv_bfloat16* __restrict__ sv, int N, int unit) {
    const uint32_t sbase = smem_u32(smem);
    const uint32_t ubase = __reduce_or_sync(0xffffffffu, sbase + unit * STAGES * STAGE_BYTES);
    const int* misc = reinterpret_cast<const int*>(smem + MS_MISC);
    const int ln = pin(threadIdx.x & 31);
    const int r4 = ln >> 3;
    const unsigned char* gsrc = g_tab + (ln & 7) * 16;
    asm volatile("" : "+l"(gsrc));
    const uint32_t d0 = r4 * 128 + (((ln & 7) ^ r4) << 4);
    const uint32_t goff = ST_G + ln * 32 + (((ln >> 2) & 1) << 4);
    const uint32_t roff = ST_R + ((ln >> 1) & 3) * 16 + (ln >> 3) * 4 + (ln & 1) * 2;
    const unsigned char* ghot = smem + (MS_GH - HOT0 * 32);
    const unsigned char* gcold = reinterpret_cast<const unsigned char*>(g_G);
    asm volatile("" : "+l"(ghot), "+l"(gcold));
    uint32_t sb = ubase, ph = 1;
    const int tv = ln < NQ ? misc[ln] : 0;
    const int total = __reduce_add_sync(0xffffffffu, tv);
    const int s1 = total / 3, s2 = (2 * total) / 3;
    const int un = (int)__reduce_or_sync(0xffffffffu, (uint32_t)unit);
    const int ulo = un == 0 ? 0 : (un == 1 ? s1 : s2);
    const int uhi = un == 0 ? s1 : (un == 1 ? s2 : total);
    const int nnodes = min(NPC, N - (int)blockIdx.x * NPC);
    int gb = 0;
    for (int q = 0; q < NQ; q++) {
        const int gcnt = __reduce_add_sync(0xffffffffu, ln == q ? tv : 0);
        const int ge = gb + gcnt;
        const int beg = gb;
        gb = ge;
        const bool own = beg >= ulo && (beg < uhi || un == 2);
        const int lo = max(beg, ulo), hi = min(ge, uhi);
        if (!own && lo >= hi) continue;
        uint32_t ra = sbase + MS_REC + (lo + ln) * 8;
        const int cnt = hi - beg;
        int rem = max(hi - lo, 0);
        const int lastcap = own ? 24 : 32;
        uint32_t flast = own ? 2u : 4u;
        if (own && un == 0 && beg < s1 && s1 < ge && s1 < s2) flast |= 16u;
        if (own && un < 2 && beg < s2 && s2 < ge) flast |= 32u;
        const unsigned char* svp = reinterpret_cast<const unsigned char*>(sv) +
                                   (size_t)(blockIdx.x * NPC + q * GRP + r4) * 512 + (ln & 7) * 16;
        auto fetch = [&](int left) -> uint2 {
            uint2 r = make_uint2(0, 0);
            if (FITS) {
                asm volatile("ld.shared.v2.u32 {%0,%1}, [%2];" : "=r"(r.x), "=r"(r.y) : "r"(ra));
                ra += 256;
            } else if (ln < left) {
                const int j = cnt - left + ln;
                const int* prq = reinterpret_cast<const int*>(smem + MS_B2) + q * 136;
                int lo = 0, hi = NCTA;
                while (hi - lo > 1) {
                    const int mid = (lo + hi) >> 1;
                    if (prq[mid] <= j) lo = mid; else hi = mid;
                }
                const int b0 = __ldcg(reinterpret_cast<const unsigned short*>(g_pfx + (lo * NCTA + blockIdx.x) * 2) + q + (q >= 7));
                r = __ldcg(g_rec + lo * CH + b0 + (j - prq[lo]));
            }
            return r;
        };
        uint2 rn = fetch(rem);
        bool last;
        do {
            const bool valid = ln < rem;
            last = rem <= lastcap;
            const bool svl = last && own;
            const uint2 r = valid ? rn : make_uint2(0, 0);
            rn = fetch(rem - 32);
            const uint32_t srcv = (r.y >> 16) & 0x7fffu;
            const unsigned char* gq[8];
#pragma unroll
            for (int k = 0; k < 8; k++)
                gq[k] = gsrc + (size_t)__shfl_sync(0xffffffffu, srcv, k * 4 + r4) * ROWB;
            const int lim = rem - r4;
            const int lim6 = svl ? nnodes - q * GRP + 24 - r4 : lim;
            if (svl) { gq[6] = svp; gq[7] = svp + 4 * 512; }
            const uint32_t rxy = hmul2(r.x & 0x9fff9fffu, 0x60806080u);
            const uint32_t rz2 = hmul2(r.y & 0x00009fffu, 0x60806080u);
            const uint32_t qxy = hmul2(rxy, rxy), qz = hmul2(rz2, rz2);
            const float sum = bf16r((__uint_as_float(qxy << 16) + __uint_as_float(qxy & 0xffff0000u)) + __uint_as_float(qz << 16));
            float sq;
            asm("sqrt.approx.ftz.f32 %0, %1;" : "=f"(sq) : "f"(bf16r(sum + 1e-8f)));
            const uint32_t dbits = pack_bf16(0.f, sq);
            float rinv;
            asm("rcp.approx.ftz.f32 %0, %1;" : "=f"(rinv) : "f"(__uint_as_float(dbits)));
            const int di = valid ? max(min((int)(dbits >> 16), DEND - 1) - DBASE, 0) : NTAB - 1;
            const uint4* gp = reinterpret_cast<const uint4*>(di >= HOT0 ? ghot : gcold) + 2 * di;
            const uint4 g0 = gp[0], g1 = gp[1];
            const uint32_t r01 = pack_bf16(__uint_as_float(rxy << 16) * rinv, __uint_as_float(rxy & 0xffff0000u) * rinv);
            const uint32_t r2 = pack_bf16(__uint_as_float(rz2 << 16) * rinv, valid ? 1.0f : 0.f);
            const uint32_t so = ((r.x >> 12) & 6u) | ((r.x >> 26) & 8u);
            const uint32_t fl = last ? (((uint32_t)q << 8) | flast) : 0u;

            const uint32_t bar = sb + ST_CTL;
            mbar_wait(bar + 8, ph);
            const uint32_t dpa = sb + d0, dpb = (dpa ^ 64u) + 512u;
#pragma unroll
            for (int k = 0; k < 8; k++) {
                asm volatile("{\n.reg .pred p;\nsetp.le.s32 p, %2, %3;\n"
                             "cp.async.cg.shared.global [%0], [%1], 16, p;\n"
                             "cp.async.cg.shared.global [%0+4096], [%1+128], 16, p;\n"
                             "cp.async.cg.shared.global [%0+8192], [%1+256], 16, p;\n"
                             "cp.async.cg.shared.global [%0+12288], [%1+384], 16, p;\n}\n"
                             ::"r"(((k & 1) ? dpb : dpa) + (k >> 1) * 1024), "l"(gq[k]), "r"(k < 6 ? lim : lim6), "r"(4 * k) : "memory");
            }
            asm volatile("cp.async.mbarrier.arrive.noinc.shared::cta.b64 [%0];" ::"r"(bar) : "memory");
            const uint32_t za = sb + ST_S + ln * 16;
            asm volatile("st.shared.v4.u32 [%0], {%1,%1,%1,%1};" ::"r"(za), "r"(0u) : "memory");
            asm volatile("st.shared.u16 [%0], %1;" ::"r"(za + so), "h"((unsigned short)(r2 >> 16)) : "memory");
            asm volatile("st.shared.u16 [%0], %1;" ::"r"(sb + roff), "h"((unsigned short)(r01 & 0xffffu)) : "memory");
            asm volatile("st.shared.u16 [%0+64], %1;" ::"r"(sb + roff), "h"((unsigned short)(r01 >> 16)) : "memory");
            asm volatile("st.shared.u16 [%0+128], %1;" ::"r"(sb + roff), "h"((unsigned short)(r2 & 0xffffu)) : "memory");
            asm volatile("st.shared.u32 [%0+16], %1;" ::"r"(bar), "r"(fl) : "memory");
            asm volatile("st.shared.v4.u32 [%0], {%1,%2,%3,%4};" ::"r"(sb + goff),
                         "r"(g0.x), "r"(g0.y), "r"(g0.z), "r"(g0.w) : "memory");
            asm volatile("st.shared.v4.u32 [%0], {%1,%2,%3,%4};" ::"r"((sb + goff) ^ 16u),
                         "r"(g1.x), "r"(g1.y), "r"(g1.z), "r"(g1.w) : "memory");
            asm volatile("fence.proxy.async.shared::cta;" ::: "memory");
            mbar_arrive(bar);
            sb += STAGE_BYTES;
            if (sb == ubase + STAGES * STAGE_BYTES) { sb = ubase; ph ^= 1; }
            rem -= 32;
        } while (!last);
    }
    const uint32_t bar = sb + ST_CTL;
    mbar_wait(bar + 8, ph);
    asm volatile("st.shared.u32 [%0+16], %1;" ::"r"(bar), "r"(8u) : "memory");
    mbar_arrive(bar);
    mbar_arrive(bar);
}

__global__ void __launch_bounds__(M_THREADS, 1)
fused_kernel(const __nv_bfloat16* __restrict__ sv, const __nv_bfloat16* __restrict__ pos,
             const int* __restrict__ src, const int* __restrict__ dst,
             const __nv_bfloat16* __restrict__ freqs, const __nv_bfloat16* __restrict__ w1,
             const __nv_bfloat16* __restrict__ w2, const __nv_bfloat16* __restrict__ wrbf,
             __nv_bfloat16* __restrict__ out, int N, int E) {
    extern __shared__ __align__(1024) unsigned char smem[];
    const int tid = threadIdx.x, lane = tid & 31;
    const int warp = (int)__reduce_or_sync(0xffffffffu, (uint32_t)tid >> 5);
    const uint32_t sbase = smem_u32(smem);
    const uint32_t ghbar = sbase + MS_BAR;
    int* misc = reinterpret_cast<int*>(smem + MS_MISC);
    const bool is_prod = warp >= UNITS * 4;
    const int cta = blockIdx.x;
    const int nnodes = min(NPC, N - cta * NPC);

    STAMP(0, 0);
    const int e0 = cta * EPC;
    const int ne = max(min(EPC, E - e0), 0);
    if (tid == 0) {
        mbar_init(ghbar, 1);
        mbar_init(ghbar + 8, 128);
        mbar_init(ghbar + 16, 128);
        mbar_init(ghbar + 24, 1);
        asm volatile("fence.mbarrier_init.release.cluster;" ::: "memory");
        mbar_expect_tx(ghbar + 24, ne * 8 + N * 6);
        if (ne > 0) {
            bulk_g2s(sbase + PS_SRC, src + e0, ne * 4, ghbar + 24);
            bulk_g2s(sbase + PS_DST, dst + e0, ne * 4, ghbar + 24);
        }
        bulk_g2s(sbase + PS_POS, pos, N * 6, ghbar + 24);
    }
    unsigned int epoch;
    asm volatile("ld.relaxed.gpu.global.u32 %0, [%1];" : "=r"(epoch) : "l"(&g_cnt));
    int* hist = reinterpret_cast<int*>(smem + PS_HIST);
    hist[tid] = 0; hist[tid + 512] = 0; hist[tid + 1024] = 0;
    cp_async16(sbase + PS_W1 + (tid >> 3) * 144 + (tid & 7) * 16, w1 + tid * 8);
    for (int i = tid; i < 80 * 24; i += M_THREADS) {
        const int r = i / 24, c = i - r * 24;
        const int o = r >= 64 ? PS_WR + (r - 64) * 400 + c * 16
                              : ((c >> 3) == 1 ? PS_WV + r * 144 + (c - 8) * 16 : PS_W2 + r * 272 + (c & 7) * 16 + (c >> 4) * 128);
        cp_async16(sbase + o, (r < 64 ? w2 : wrbf - 64 * 192) + i * 8);
    }
    __syncthreads();
    mbar_wait(ghbar + 24, 0);
    STAMP(1, 0);
    if (!is_prod) {
#pragma unroll
        for (int k = 0; k < 2; k++) {
            const int row = (warp & 3) * 8 + k * 4 + (lane >> 3);
            const int node = (warp >> 2) * 32 + row;
            asm volatile("{\n.reg .pred p;\nsetp.ge.s32 p, %2, %3;\n"
                         "cp.async.cg.shared.global [%0], [%1], 16, p;\n"
                         "cp.async.cg.shared.global [%0+4096], [%1+128], 16, p;\n"
                         "cp.async.cg.shared.global [%0+8192], [%1+256], 16, p;\n"
                         "cp.async.cg.shared.global [%0+12288], [%1+384], 16, p;\n}\n"
                         ::"r"(sbase + (warp >> 2) * STAGE_BYTES + row * 128 + (((lane ^ row) & 7) << 4)),
                           "l"(sv + (size_t)(cta * NPC + min(node, nnodes - 1)) * 256 + (lane & 7) * 8), "r"(node), "r"(nnodes) : "memory");
        }
    }
    {
        int2* ps = reinterpret_cast<int2*>(smem + PS_SRC);
        int2* pd = reinterpret_cast<int2*>(smem + PS_DST);
        int2* pk = reinterpret_cast<int2*>(smem + PS_KEY);
        const int np = ne >> 1;
#pragma unroll 1
        for (int i = tid; i < np; i += M_THREADS) {
            const int2 es = ps[i], ed = pd[i];
            int rx[2], ry[2], key[2];
#pragma unroll
            for (int b = 0; b < 2; b++) {
                const uint32_t sn = b ? es.y : es.x, dn = b ? ed.y : ed.x;
                const uint32_t as = sbase + PS_POS + sn * 6, ad = sbase + PS_POS + dn * 6;
                uint32_t sa, sb, da, db;
                asm volatile("ld.shared.u32 %0, [%2];\nld.shared.u32 %1, [%2+4];" : "=r"(sa), "=r"(sb) : "r"(as & ~3u));
                asm volatile("ld.shared.u32 %0, [%2];\nld.shared.u32 %1, [%2+4];" : "=r"(da), "=r"(db) : "r"(ad & ~3u));
                const uint32_t rxy = hsub2(__funnelshift_r(sa, sb, as << 3), __funnelshift_r(da, db, ad << 3));
                const uint32_t rz = hsub2(__funnelshift_r(sb, 0u, as << 3), __funnelshift_r(db, 0u, ad << 3));
                const uint32_t qxy = hmul2(rxy, rxy), qz = hmul2(rz, rz);
                const float sum = (__uint_as_float(qxy << 16) + __uint_as_float(qxy & 0xffff0000u)) + __uint_as_float(qz << 16);
                const uint32_t c = dn / NPC, dl = dn - c * NPC;
                rx[b] = hmul2(rxy, 0x1e801e80u) | ((dl * 0x08002000u) & 0x60006000u);
                ry[b] = __byte_perm(hmul2(rz, 0x1e801e80u), sn, 0x5410) | ((dl * 0x02000200u) & 0x80006000u);
                const int bin = c * NQ + (dl >> 3);
                key[b] = -1;
                if (sum < 23.9375f) key[b] = (bin << 13) | atomicAdd(&hist[bin], 1);
            }
            ps[i] = make_int2(rx[0], rx[1]);
            pd[i] = make_int2(ry[0], ry[1]);
            pk[i] = make_int2(key[0], key[1]);
        }
        __syncthreads();
        STAMP(2, 0);
        const int h0 = hist[3 * tid], h1 = hist[3 * tid + 1], h2 = hist[3 * tid + 2];
        int incl = h0 + h1 + h2;
#pragma unroll
        for (int o = 1; o < 32; o <<= 1) {
            const int v = __shfl_up_sync(0xffffffffu, incl, o);
            if (lane >= o) incl += v;
        }
        if (lane == 31) hist[1536 + warp] = incl;
        __syncthreads();
        const int ex = __reduce_add_sync(0xffffffffu, lane < warp ? hist[1536 + lane] : 0) + incl - h2;
        hist[3 * tid] = ex - h1 - h0; hist[3 * tid + 1] = ex - h1; hist[3 * tid + 2] = ex;
        __syncthreads();
        STAMP(3, 0);
        int2* sorted = reinterpret_cast<int2*>(smem + PS_POS);
#pragma unroll 1
        for (int i = tid; i < np; i += M_THREADS) {
            const int2 k = pk[i], x = ps[i], y = pd[i];
            if (k.x >= 0) sorted[hist[k.x >> 13] + (k.x & 8191)] = make_int2(x.x, y.x);
            if (k.y >= 0) sorted[hist[k.y >> 13] + (k.y & 8191)] = make_int2(x.y, y.y);
        }
        __syncthreads();
        STAMP(4, 0);
        const int n16 = (hist[NBIN] + 1) >> 1;
#pragma unroll 1
        for (int i = tid; i < n16; i += M_THREADS)
            reinterpret_cast<uint4*>(g_rec + cta * CH)[i] = reinterpret_cast<const uint4*>(smem + PS_POS)[i];
        asm volatile("cp.async.wait_all;" ::: "memory");
        asm volatile("fence.proxy.async.shared::cta;" ::: "memory");
        __syncthreads();
        STAMP(5, 0);
    }
    epoch /= NCTA;
    const uint32_t tag = ((epoch + 1) & 0xffffu) << 16;
    const int g = lane >> 2, t = lane & 3;
    if (is_prod) {
        __threadfence();
        for (int c = tid - 384; c < NCTA; c += 128) {
            const int* h = hist + c * NQ;
            asm volatile("st.relaxed.gpu.global.v4.u32 [%0], {%1,%2,%3,%4};" ::"l"(g_pfx + (cta * NCTA + c) * 2),
                         "r"(h[0] | (h[1] << 16)), "r"(h[2] | (h[3] << 16)), "r"(h[4] | (h[5] << 16)), "r"(h[6] | tag) : "memory");
            asm volatile("st.relaxed.gpu.global.v4.u32 [%0], {%1,%2,%3,%4};" ::"l"(g_pfx + (cta * NCTA + c) * 2 + 1),
                         "r"(h[7] | (h[8] << 16)), "r"(h[9] | (h[10] << 16)), "r"(0), "r"(tag) : "memory");
        }
        STAMP(6, 384);
        if (tid < 384 + UNITS * STAGES) {
            mbar_init(sbase + (tid - 384) * STAGE_BYTES + ST_CTL, 64);
            mbar_init(sbase + (tid - 384) * STAGE_BYTES + ST_CTL + 8, 4);
            asm volatile("fence.mbarrier_init.release.cluster;" ::: "memory");
        }
#pragma unroll 1
        for (int gi = cta * 128 + tid - 384; gi < NTAB * NRBF; gi += NCTA * 128) {
            const float d = __uint_as_float((uint32_t)(DBASE + (gi >> 4)) << 16);
            const float arg = bf16r(d * __bfloat162float(freqs[gi & 15]));
            float sn;
            if (fabsf(arg) < 1000.f) {
                const float k = rintf(arg * 0.15915494309189535f);
                sn = __sinf(fmaf(k, 1.7484556000744883e-7f, fmaf(k, -6.2831854820251465f, arg)));
            } else {
                sn = sinf(arg);
            }
            const float rbf = bf16r(__fdividef(bf16r(sn), d));
            const float ca = bf16r(bf16r(3.14159265358979f * d) * 0.2f);
            const float fc = 0.5f * bf16r(bf16r(__cosf(ca)) + 1.0f);
            g_G[gi] = __float2bfloat16_rn(rbf * fc);
        }
        STAMP(7, 384);
    } else {
        const int w = warp & 3;
        const uint32_t tb = __reduce_or_sync(0xffffffffu, sbase + (warp >> 2) * STAGE_BYTES);
        const int krow = (lane & 7) + 8 * (lane >> 4), mcol = 2 * w + ((lane >> 3) & 1);
        const uint32_t ta = tb + krow * 128 + ((uint32_t)(mcol ^ (lane & 7)) << 4);
        const uint32_t dh = (tb >> 4) | (1u << 16);
        uint32_t a[4][4];
        float d[16];
#pragma unroll
        for (int q = 0; q < 4; q++) ldsm4t(a[q], sbase + PS_W1 + (16 * q + krow) * 144 + mcol * 16);
        asm volatile("wgmma.fence.sync.aligned;" ::: "memory");
        wgmma_n32<0, DESC_H>(d, a[0], dh);
        wgmma_n32<1, DESC_H>(d, a[1], dh + 2);
        wgmma_n32<1, DESC_H>(d, a[2], dh + 4);
        wgmma_n32<1, DESC_H>(d, a[3], dh + 6);
        asm volatile("wgmma.commit_group.sync.aligned;" ::: "memory");
        asm volatile("wgmma.wait_group.sync.aligned 0;" ::: "memory");
        reg_fence16(d);
#pragma unroll
        for (int q = 0; q < 4; q++) ldsm4t(a[q], sbase + PS_WV + (16 * q + krow) * 144 + mcol * 16);
        uint32_t x[2][4];
#pragma unroll
        for (int i = 0; i < 8; i++) {
            const uint32_t z = pack_bf16(d[2 * i], d[2 * i + 1]);
            const float z0 = __uint_as_float(z << 16), z1 = __uint_as_float(z & 0xffff0000u);
            x[i >> 2][i & 3] = pack_bf16(__fdividef(z0, 1.0f + __expf(-z0)), __fdividef(z1, 1.0f + __expf(-z1)));
        }
        asm volatile("bar.sync %0, 128;" ::"r"(1 + (warp >> 2)) : "memory");
        stsm4t(ta, x[0]);
        stsm4t(ta + 2048, x[1]);
        asm volatile("fence.proxy.async.shared::cta;" ::: "memory");
        asm volatile("bar.sync %0, 128;" ::"r"(1 + (warp >> 2)) : "memory");
        asm volatile("wgmma.fence.sync.aligned;" ::: "memory");
        wgmma_n32<0, DESC_H>(d, a[0], dh);
        wgmma_n32<1, DESC_H>(d, a[1], dh + 2);
        wgmma_n32<1, DESC_H>(d, a[2], dh + 4);
        wgmma_n32<1, DESC_H>(d, a[3], dh + 6);
        asm volatile("wgmma.commit_group.sync.aligned;" ::: "memory");
        asm volatile("wgmma.wait_group.sync.aligned 0;" ::: "memory");
        reg_fence16(d);
#pragma unroll
        for (int i = 0; i < 8; i++) x[i >> 2][i & 3] = pack_bf16(d[2 * i], d[2 * i + 1]);
#pragma unroll
        for (int j = 1; j < 4; j++)
#pragma unroll
            for (int s = 0; s < 2; s++) {
                uint32_t v[4];
                ldsm4t(v, ta + j * 4096 + s * 2048);
#pragma unroll
                for (int e = 0; e < 4; e++) v[e] = hmul2(v[e], x[s][e]);
                stsm4t(ta + j * 4096 + s * 2048, v);
            }
        asm volatile("bar.sync %0, 128;" ::"r"(1 + (warp >> 2)) : "memory");
#pragma unroll
        for (int k = 0; k < 2; k++) {
            const int row = w * 8 + k * 4 + (lane >> 3);
            const int node = (warp >> 2) * 32 + row;
            if (node < nnodes) {
                uint4* o = reinterpret_cast<uint4*>(g_tab + (size_t)(cta * NPC + node) * ROWB) + (lane & 7);
                const unsigned char* ip = smem + (warp >> 2) * STAGE_BYTES + row * 128 + (((lane ^ row) & 7) << 4);
#pragma unroll
                for (int c = 0; c < 4; c++) o[c * 8] = *reinterpret_cast<const uint4*>(ip + c * 4096);
            }
        }
        STAMP(8, 0);
    }
    __syncthreads();
    if (tid == M_THREADS - 1) {
        __threadfence();
        atomicInc(&g_cnt, NCTA * 65536u - 1);
    }
    STAMP(9, 0);

    {
        unsigned short* pf = reinterpret_cast<unsigned short*>(smem + PS_PF);
        int* b2 = reinterpret_cast<int*>(smem + MS_B2);
        if (tid < NCTA) {
            const uint4* bp = g_pfx + (tid * NCTA + cta) * 2;
            uint4 b0, b1;
            int spin = 0;
            do {
                asm volatile("ld.relaxed.gpu.global.v4.u32 {%0,%1,%2,%3}, [%4];" : "=r"(b0.x), "=r"(b0.y), "=r"(b0.z), "=r"(b0.w) : "l"(bp) : "memory");
                asm volatile("ld.relaxed.gpu.global.v4.u32 {%0,%1,%2,%3}, [%4];" : "=r"(b1.x), "=r"(b1.y), "=r"(b1.z), "=r"(b1.w) : "l"(bp + 1) : "memory");
            } while ((((b0.w ^ tag) | (b1.w ^ tag)) & 0xffff0000u) && ++spin < (1 << 22));
            __threadfence();
            reinterpret_cast<uint4*>(pf)[tid * 2] = make_uint4(b0.x, b0.y, b0.z, __byte_perm(b0.w, b1.x, 0x5410));
            reinterpret_cast<uint2*>(pf)[tid * 4 + 2] = make_uint2(__byte_perm(b1.x, b1.y, 0x5432), b1.y >> 16);
        }
        __syncthreads();
        STAMP(10, 0);
#pragma unroll 1
        for (int p = warp; p < NCTA; p += 16) {
            const int i = (pf[p * 16] & ~1) + 2 * lane;
            if (i < pf[p * 16 + NQ])
                cp_async16(sbase + (3 + (p >> 5)) * STAGE_BYTES + (p & 31) * 512 + lane * 16, g_rec + p * CH + i);
        }
        int lo[5], cq[5], pre = 0;
        if (warp < NQ) {
            int sum = 0;
#pragma unroll
            for (int k = 0; k < 5; k++) {
                const int p = min(lane * 5 + k, NCTA - 1);
                lo[k] = pf[p * 16 + warp];
                cq[k] = lane * 5 + k < NCTA ? pf[p * 16 + warp + 1] - lo[k] : 0;
                sum += cq[k];
            }
            int in2 = sum;
#pragma unroll
            for (int o = 1; o < 32; o <<= 1) {
                const int v = __shfl_up_sync(0xffffffffu, in2, o);
                if (lane >= o) in2 += v;
            }
            pre = in2 - sum;
            if (lane == 31) misc[warp] = in2;
        }
        __syncthreads();
        const int tv = lane < NQ ? misc[lane] : 0;
        const bool fits = __reduce_add_sync(0xffffffffu, tv) <= RCAP;
        if (warp < NQ) {
            if (fits) pre += __reduce_add_sync(0xffffffffu, lane < warp ? tv : 0);
#pragma unroll
            for (int k = 0; k < 5; k++) {
                if (lane * 5 + k < NCTA) b2[warp * 136 + lane * 5 + k] = fits ? pre - lo[k] : pre;
                pre += cq[k];
            }
        }
        asm volatile("cp.async.wait_all;" ::: "memory");
        __syncthreads();
        STAMP(11, 0);
        if (fits) {
            uint2* srec = reinterpret_cast<uint2*>(smem + MS_REC);
#pragma unroll 1
            for (int p = warp; p < NCTA; p += 16) {
                const int beg = pf[p * 16], end = pf[p * 16 + NQ];
                const uint2* raw = reinterpret_cast<const uint2*>(smem + (3 + (p >> 5)) * STAGE_BYTES + (p & 31) * 512);
#pragma unroll 1
                for (int i = beg + lane; i < end; i += 32) {
                    const int o = i - (beg & ~1);
                    const uint2 v = o < 64 ? raw[o] : __ldcg(g_rec + p * CH + i);
                    const int q = (int)(((v.x >> 30) & 1u) | ((v.y >> 12) & 6u) | ((v.y >> 28) & 8u));
                    srec[b2[q * 136 + p] + i] = v;
                }
            }
        }
        __syncthreads();
    }
    STAMP(12, 0);

    if (is_prod) {
        asm volatile("setmaxnreg.dec.sync.aligned.u32 80;");
        const int unit = warp - UNITS * 4;
        if (unit < UNITS) {
            if (unit == 0) asm volatile("bar.sync 4, 416;" ::: "memory");
            {
                const unsigned int ep = __reduce_or_sync(0xffffffffu, epoch);
                unsigned int c;
                int spin = 0;
                do {
                    asm volatile("ld.acquire.gpu.global.u32 %0, [%1];" : "=r"(c) : "l"(&g_cnt) : "memory");
                    c = __reduce_or_sync(0xffffffffu, c);
                } while (c / NCTA == ep && ++spin < (1 << 22));
                if (unit == 0) {
                    asm volatile("fence.proxy.async.global;" ::: "memory");
                    asm volatile("{\n.reg .pred p;\nelect.sync _|p, 0xffffffff;\n"
                                 "@p mbarrier.arrive.expect_tx.shared::cta.b64 _, [%0], %1;\n"
                                 "@p cp.async.bulk.shared::cluster.global.mbarrier::complete_tx::bytes [%2], [%3], %1, [%0];\n}\n"
                                 ::"r"(ghbar), "r"((NTAB - HOT0) * 32), "r"(sbase + MS_GH), "l"(g_G + HOT0 * NRBF) : "memory");
                    STAMP(13, 384);
                }
            }
            mbar_wait(ghbar, 0);
            STAMP(21, 384);
            if (__reduce_add_sync(0xffffffffu, lane < NQ ? misc[lane] : 0) <= RCAP) producer_loop<true>(smem, sv, N, unit);
            else producer_loop<false>(smem, sv, N, unit);
            STAMP(22 + unit, 384 + 32 * unit);
        }
    } else {
        asm volatile("setmaxnreg.inc.sync.aligned.u32 144;");
        const int unit = warp >> 2, w = warp & 3;
        const uint32_t ubase = sbase + unit * STAGES * STAGE_BYTES;
        uint32_t wa[3][4], pa[2][4][4];
        {
            const int krow = (lane & 7) + 8 * (lane >> 4), mcol = 2 * w + ((lane >> 3) & 1);
#pragma unroll
            for (int q = 0; q < 4; q++) {
                ldsm4t(pa[0][q], sbase + PS_W2 + (16 * q + krow) * 272 + mcol * 16);
                ldsm4t(pa[1][q], sbase + PS_W2 + (16 * q + krow) * 272 + 128 + mcol * 16);
            }
#pragma unroll
            for (int p = 0; p < 3; p++) ldsm4t(wa[p], sbase + PS_WR + krow * 400 + p * 128 + mcol * 16);
            asm volatile("bar.sync 4, 416;" ::: "memory");
        }
        float acc[4][4];
#pragma unroll
        for (int c = 0; c < 4; c++)
#pragma unroll
            for (int e = 0; e < 4; e++) acc[c][e] = 0.f;
        const int erow = (lane & 7) + 8 * (lane >> 4);
        const int ehalf = (lane >> 3) & 1;
        const uint32_t ua = pin(4096 + erow * 128 + ((uint32_t)((2 * w + ehalf) ^ (lane & 7)) << 4));
        const uint32_t sa = pin(ST_S + lane * 16);
        const uint32_t ra = pin(ST_R + t * 16);
        const uint32_t ub = __reduce_or_sync(0xffffffffu, ubase);
        uint32_t sb = ub;
        uint32_t ph = 0;
        const bool elected = sa == ST_S;
        while (true) {
            mbar_wait(sb + ST_CTL, ph);
            {
                const uint32_t dh = (sb >> 4) | (1u << 16);
                const uint32_t dg = dh + (ST_G >> 4);
                uint32_t m[2][4], wv[2][4], u[3][4], sf[4], rr[3][2];
                float p0[16], f0[16], fv[16];
                asm volatile("wgmma.fence.sync.aligned;" ::: "memory");
                wgmma_n32<0, DESC_G>(f0, wa[2], dg);
                wgmma_n32<0, DESC_H>(p0, pa[1][0], dh);
                wgmma_n32<1, DESC_H>(p0, pa[1][1], dh + 2);
                wgmma_n32<1, DESC_H>(p0, pa[1][2], dh + 4);
                wgmma_n32<1, DESC_H>(p0, pa[1][3], dh + 6);
                wgmma_n32<0, DESC_G>(fv, wa[1], dg);
                asm volatile("wgmma.commit_group.sync.aligned;" ::: "memory");
#pragma unroll
                for (int j = 0; j < 3; j++) {
                    ldsm4t(u[j], sb + ua + j * 4096);
                    asm volatile("ld.shared.v2.u32 {%0,%1}, [%2];" : "=r"(rr[j][0]), "=r"(rr[j][1]) : "r"(sb + ra + j * 64));
                }
                ldsm4t(sf, sb + sa);
                asm volatile("wgmma.wait_group.sync.aligned 0;" ::: "memory");
                reg_fence16(fv); reg_fence16(f0); reg_fence16(p0);
#pragma unroll
                for (int i = 0; i < 8; i++) {
                    m[i >> 2][i & 3] = pack_bf16(f0[2 * i] * p0[2 * i], f0[2 * i + 1] * p0[2 * i + 1]);
                    wv[i >> 2][i & 3] = pack_bf16(fv[2 * i], fv[2 * i + 1]);
                }
                asm volatile("wgmma.fence.sync.aligned;" ::: "memory");
                wgmma_n32<0, DESC_G>(f0, wa[0], dg);
                wgmma_n32<0, DESC_H>(p0, pa[0][0], dh);
                wgmma_n32<1, DESC_H>(p0, pa[0][1], dh + 2);
                wgmma_n32<1, DESC_H>(p0, pa[0][2], dh + 4);
                wgmma_n32<1, DESC_H>(p0, pa[0][3], dh + 6);
                asm volatile("wgmma.commit_group.sync.aligned;" ::: "memory");
                uint32_t v1[3][4];
#pragma unroll
                for (int j = 0; j < 3; j++)
#pragma unroll
                    for (int e = 0; e < 4; e++) u[j][e] = hfma2(m[0][e], rr[j][e >> 1], hmul2(u[j][e], wv[0][e]));
#pragma unroll
                for (int j = 0; j < 3; j++) {
                    ldsm4t(v1[j], sb + ua + j * 4096 + 2048);
                    asm volatile("ld.shared.v2.u32 {%0,%1}, [%2];" : "=r"(rr[j][0]), "=r"(rr[j][1]) : "r"(sb + ra + j * 64 + 8));
                }
#pragma unroll
                for (int j = 0; j < 3; j++)
#pragma unroll
                    for (int e = 0; e < 4; e++) v1[j][e] = hfma2(m[1][e], rr[j][e >> 1], hmul2(v1[j][e], wv[1][e]));
#pragma unroll
                for (int j = 0; j < 3; j++) mma16816(acc[j + 1], u[j], sf[0], sf[1]);
#pragma unroll
                for (int j = 0; j < 3; j++) mma16816(acc[j + 1], v1[j], sf[2], sf[3]);
                asm volatile("wgmma.wait_group.sync.aligned 0;" ::: "memory");
                reg_fence16(f0); reg_fence16(p0);
#pragma unroll
                for (int i = 0; i < 8; i++)
                    m[i >> 2][i & 3] = pack_bf16(f0[2 * i] * p0[2 * i], f0[2 * i + 1] * p0[2 * i + 1]);
                mma16816(acc[0], m[0], sf[0], sf[1]);
                mma16816(acc[0], m[1], sf[2], sf[3]);
            }
            uint32_t flags;
            asm volatile("ld.shared.u32 %0, [%1+16];" : "=r"(flags) : "r"(sb + ST_CTL));
            if (flags) {
                if (flags & 8u) break;
                float* part = reinterpret_cast<float*>(smem + MS_PART) + (tid & 127);
                if (flags & 4u) {
#pragma unroll
                    for (int i = 0; i < 16; i++) part[(unit - 1) * 2048 + i * 128] = acc[i >> 2][i & 3];
                    mbar_arrive(sbase + MS_BAR + unit * 8);
                } else {
#pragma unroll 1
                    for (int k = 0; k < 2; k++) {
                        if (flags & (16u << k)) {
                            mbar_wait(sbase + MS_BAR + 8 + k * 8, 0);
#pragma unroll
                            for (int i = 0; i < 16; i++) acc[i >> 2][i & 3] += part[k * 2048 + i * 128];
                        }
                    }
                    const uint32_t ea = sb + (lane >> 4) * 4096 + (24 + (lane & 7)) * 128 +
                                        ((uint32_t)((2 * w + ((lane >> 3) & 1)) ^ (lane & 7)) << 4);
#pragma unroll
                    for (int k = 0; k < 2; k++) {
                        uint32_t v[4];
                        ldsm4t(v, ea + k * 8192);
#pragma unroll
                        for (int e = 0; e < 4; e++)
                            v[e] = pack_bf16(__uint_as_float(v[e] << 16) + acc[2 * k + (e >> 1)][2 * (e & 1)],
                                             __uint_as_float(v[e] & 0xffff0000u) + acc[2 * k + (e >> 1)][2 * (e & 1) + 1]);
                        stsm4t(ea + k * 8192, v);
                    }
                    __syncwarp();
                    const int ln0 = (int)(flags >> 8) * GRP + (lane >> 2);
                    const int c0 = (lane >> 1) & 1, ch = 2 * w + (lane & 1);
                    uint4* op = reinterpret_cast<uint4*>(out + (size_t)(blockIdx.x * NPC + ln0) * 256) + c0 * 8 + ch;
                    const uint32_t ia = sb + c0 * 4096 + (24 + (lane >> 2)) * 128 + ((uint32_t)(ch ^ (lane >> 2)) << 4);
#pragma unroll
                    for (int k = 0; k < 2; k++) {
                        asm volatile("{\n.reg .pred p;\n.reg .b32 a, b, c, d;\nsetp.lt.s32 p, %2, %3;\n"
                                     "ld.shared.v4.u32 {a, b, c, d}, [%0];\n"
                                     "@p st.global.v4.u32 [%1], {a, b, c, d};\n}\n"
                                     ::"r"(ia + k * 8192), "l"(op + k * 16), "r"(ln0), "r"(min(NPC, N - (int)blockIdx.x * NPC)) : "memory");
                    }
                }
#pragma unroll
                for (int i = 0; i < 16; i++) acc[i >> 2][i & 3] = 0.f;
            }
            __syncwarp();
            if (elected) mbar_arrive(sb + ST_CTL + 8);
            sb += STAGE_BYTES;
            if (sb == ub + STAGES * STAGE_BYTES) { sb = ub; ph ^= 1; }
        }
        STAMP(26 + unit, 128 * unit);
    }
}

}

extern "C" void kernel_launch(void* const* d_in, const int* in_sizes, int n_in, void* d_out, int out_size) {
    const __nv_bfloat16* sv = (const __nv_bfloat16*)d_in[0];
    const __nv_bfloat16* pos = (const __nv_bfloat16*)d_in[1];
    const int* src = (const int*)d_in[2];
    const int* dst = (const int*)d_in[3];
    const __nv_bfloat16* freqs = (const __nv_bfloat16*)d_in[4];
    const __nv_bfloat16* w1 = (const __nv_bfloat16*)d_in[5];
    const __nv_bfloat16* w2 = (const __nv_bfloat16*)d_in[6];
    const __nv_bfloat16* wrbf = (const __nv_bfloat16*)d_in[7];
    __nv_bfloat16* out = (__nv_bfloat16*)d_out;
    const int N = in_sizes[1] / 3;
    const int E = in_sizes[2];

    static bool init = false;
    if (!init) {
        cudaFuncSetAttribute(fused_kernel, cudaFuncAttributeMaxDynamicSharedMemorySize, M_SMEM);
        init = true;
    }
    fused_kernel<<<NCTA, M_THREADS, M_SMEM, cudaStreamPerThread>>>(sv, pos, src, dst, freqs, w1, w2, wrbf, out, N, E);
}
```

```cpp
#include <cuda_runtime.h>
#include <cuda_bf16.h>
#include <stdint.h>

namespace {

constexpr int D = 64;
constexpr int NRBF = 16;
constexpr int MAXN = 10000;
constexpr int MAXE = 640000;
constexpr int NCTA = 132;
constexpr int GRP = 8;
constexpr int NPC = (MAXN + NCTA - 1) / NCTA;
constexpr int NQ = (NPC + GRP - 1) / GRP;
constexpr int NBIN = NCTA * NQ;
constexpr int CH = 4864;
constexpr int DBASE = 0x38C0;
constexpr int DEND = 0x40A0;
constexpr int NTAB = DEND - DBASE;
constexpr int ROWB = 512;

__device__ __align__(128) unsigned char g_tab[(size_t)(MAXN + 16) * ROWB];
__device__ __align__(128) __nv_bfloat16 g_G[NTAB * NRBF];
__device__ __align__(128) uint2 g_rec[NCTA * CH];
__device__ __align__(128) uint4 g_pfx[NCTA * NCTA * 2];
__device__ unsigned int g_cnt;

#define STAMP(k, tt) do {} while (0)

__device__ __forceinline__ uint32_t smem_u32(const void* p) { return (uint32_t)__cvta_generic_to_shared(p); }
__device__ __forceinline__ uint32_t pack_bf16(float lo, float hi) {
    uint32_t r;
    asm("cvt.rn.bf16x2.f32 %0, %1, %2;" : "=r"(r) : "f"(hi), "f"(lo));
    return r;
}
__device__ __forceinline__ float bf16r(float x) { return __uint_as_float(pack_bf16(0.f, x) & 0xffff0000u); }
__device__ __forceinline__ uint32_t hmul2(uint32_t a, uint32_t b) {
    uint32_t r;
    asm("mul.rn.bf16x2 %0, %1, %2;" : "=r"(r) : "r"(a), "r"(b));
    return r;
}
__device__ __forceinline__ uint32_t hsub2(uint32_t a, uint32_t b) {
    uint32_t r;
    asm("sub.rn.bf16x2 %0, %1, %2;" : "=r"(r) : "r"(a), "r"(b));
    return r;
}
__device__ __forceinline__ uint32_t hfma2(uint32_t a, uint32_t b, uint32_t c) {
    uint32_t r;
    asm("fma.rn.bf16x2 %0, %1, %2, %3;" : "=r"(r) : "r"(a), "r"(b), "r"(c));
    return r;
}
__device__ __forceinline__ void mma16816(float (&c)[4], const uint32_t (&a)[4], uint32_t b0, uint32_t b1) {
    asm volatile("mma.sync.aligned.m16n8k16.row.col.f32.bf16.bf16.f32 {%0,%1,%2,%3}, {%4,%5,%6,%7}, {%8,%9}, {%0,%1,%2,%3};"
                 : "+f"(c[0]), "+f"(c[1]), "+f"(c[2]), "+f"(c[3])
                 : "r"(a[0]), "r"(a[1]), "r"(a[2]), "r"(a[3]), "r"(b0), "r"(b1));
}
__device__ __forceinline__ void mma16816_z(float (&c)[4], const uint32_t (&a)[4], uint32_t b0, uint32_t b1) {
    asm volatile("mma.sync.aligned.m16n8k16.row.col.f32.bf16.bf16.f32 {%0,%1,%2,%3}, {%4,%5,%6,%7}, {%8,%9}, {%10,%10,%10,%10};"
                 : "=f"(c[0]), "=f"(c[1]), "=f"(c[2]), "=f"(c[3])
                 : "r"(a[0]), "r"(a[1]), "r"(a[2]), "r"(a[3]), "r"(b0), "r"(b1), "f"(0.f));
}
__device__ __forceinline__ void ldsm4(uint32_t (&r)[4], uint32_t addr) {
    asm volatile("ldmatrix.sync.aligned.m8n8.x4.shared.b16 {%0,%1,%2,%3}, [%4];"
                 : "=r"(r[0]), "=r"(r[1]), "=r"(r[2]), "=r"(r[3]) : "r"(addr));
}
__device__ __forceinline__ void ldsm4t(uint32_t (&r)[4], uint32_t addr) {
    asm volatile("ldmatrix.sync.aligned.m8n8.x4.trans.shared.b16 {%0,%1,%2,%3}, [%4];"
                 : "=r"(r[0]), "=r"(r[1]), "=r"(r[2]), "=r"(r[3]) : "r"(addr));
}
__device__ __forceinline__ void stsm4t(uint32_t addr, const uint32_t (&r)[4]) {
    asm volatile("stmatrix.sync.aligned.m8n8.x4.trans.shared.b16 [%0], {%1,%2,%3,%4};"
                 ::"r"(addr), "r"(r[0]), "r"(r[1]), "r"(r[2]), "r"(r[3]) : "memory");
}
__device__ __forceinline__ void cp_async16(uint32_t dst, const void* src) {
    asm volatile("cp.async.cg.shared.global [%0], [%1], 16;" ::"r"(dst), "l"(src) : "memory");
}
__device__ __forceinline__ void mbar_init(uint32_t bar, int cnt) {
    asm volatile("mbarrier.init.shared::cta.b64 [%0], %1;" ::"r"(bar), "r"(cnt) : "memory");
}
__device__ __forceinline__ void mbar_arrive(uint32_t bar) {
    asm volatile("mbarrier.arrive.shared::cta.b64 _, [%0];" ::"r"(bar) : "memory");
}
__device__ __forceinline__ void mbar_expect_tx(uint32_t bar, uint32_t bytes) {
    asm volatile("mbarrier.arrive.expect_tx.shared::cta.b64 _, [%0], %1;" ::"r"(bar), "r"(bytes) : "memory");
}
__device__ __forceinline__ void mbar_wait(uint32_t bar, uint32_t parity) {
    asm volatile(
        "{\n.reg .pred p;\n.reg .u32 n;\nmov.u32 n, 0;\n"
        "WAIT_%=:\n"
        "mbarrier.try_wait.parity.shared::cta.b64 p, [%0], %1, %2;\n"
        "@p bra DONE_%=;\n"
        "add.u32 n, n, 1;\n"
        "setp.lt.u32 p, n, 100000;\n"
        "@p bra WAIT_%=;\n"
        "exit;\n"
        "DONE_%=:\n}\n" ::"r"(bar), "r"(parity), "r"(10000u) : "memory");
}
__device__ __forceinline__ void bulk_g2s(uint32_t dst, const void* src, uint32_t bytes, uint32_t bar) {
    asm volatile("cp.async.bulk.shared::cluster.global.mbarrier::complete_tx::bytes [%0], [%1], %2, [%3];"
                 ::"r"(dst), "l"(src), "r"(bytes), "r"(bar) : "memory");
}
__device__ __forceinline__ void bulk_s2g(void* dst, uint32_t src, uint32_t bytes) {
    asm volatile("cp.async.bulk.global.shared::cta.bulk_group [%0], [%1], %2;" ::"l"(dst), "r"(src), "r"(bytes) : "memory");
}

constexpr int UNITS = 3;
constexpr int STAGES = 3;
constexpr int M_THREADS = UNITS * 128 + 128;
constexpr int ST_G = 4 * 4096;
constexpr int ST_S = ST_G + 1024;
constexpr int ST_R = ST_S + 512;
constexpr int ST_CTL = ST_R + 192;
constexpr int STAGE_BYTES = ST_S + 1024;
constexpr int RCAP = 3904;
constexpr int HOT0 = 0x3F00 - DBASE;
constexpr int MS_REC = UNITS * STAGES * STAGE_BYTES;
constexpr int MS_PART = MS_REC + RCAP * 8;
constexpr int MS_GH = MS_PART + 2 * 8192;
constexpr int MS_B2 = MS_GH + (NTAB - HOT0) * 32;
constexpr int MS_MISC = MS_B2 + NQ * 136 * 4;
constexpr int MS_BAR = MS_MISC + 32 * 4;
constexpr int M_SMEM = MS_BAR + 64;
constexpr int EPC = 4852;
constexpr int PS_POS = UNITS * STAGE_BYTES;
constexpr int PS_WR = 7 * STAGE_BYTES + 4096;
constexpr int PS_PF = 7 * STAGE_BYTES + 12288;
constexpr int PS_W2 = 8 * STAGE_BYTES;
constexpr int PS_W1 = MS_REC;
constexpr int PS_WV = PS_W1 + 64 * 144;
constexpr int PS_HIST = PS_WV + 64 * 144;
static_assert(PS_POS + 60032 <= 7 * STAGE_BYTES && PS_HIST + (1536 + 32) * 4 <= MS_PART && 64 * 272 <= ST_CTL &&
              EPC * NCTA >= MAXE && EPC <= CH && CH * 8 <= 60032, "phase-1 layout");
static_assert(M_SMEM <= 232448, "smem");
static_assert(MS_BAR % 8 == 0 && MS_GH % 16 == 0 && STAGE_BYTES % 1024 == 0, "align");

template <int ACC, uint32_t HI>
__device__ __forceinline__ void wgmma_n32(float (&d)[16], const uint32_t (&a)[4], uint32_t lo) {
    if (ACC) {
        asm volatile("{\n.reg .b64 dd;\nmov.b64 dd, {%20, %21};\n"
                     "wgmma.mma_async.sync.aligned.m64n32k16.f32.bf16.bf16 {%0,%1,%2,%3,%4,%5,%6,%7,%8,%9,%10,%11,%12,%13,%14,%15}, {%16,%17,%18,%19}, dd, 1, 1, 1, 0;\n}\n"
                     : "+f"(d[0]), "+f"(d[1]), "+f"(d[2]), "+f"(d[3]), "+f"(d[4]), "+f"(d[5]), "+f"(d[6]), "+f"(d[7]),
                       "+f"(d[8]), "+f"(d[9]), "+f"(d[10]), "+f"(d[11]), "+f"(d[12]), "+f"(d[13]), "+f"(d[14]), "+f"(d[15])
                     : "r"(a[0]), "r"(a[1]), "r"(a[2]), "r"(a[3]), "r"(lo), "n"(HI));
    } else {
        asm volatile("{\n.reg .b64 dd;\nmov.b64 dd, {%20, %21};\n"
                     "wgmma.mma_async.sync.aligned.m64n32k16.f32.bf16.bf16 {%0,%1,%2,%3,%4,%5,%6,%7,%8,%9,%10,%11,%12,%13,%14,%15}, {%16,%17,%18,%19}, dd, 0, 1, 1, 0;\n}\n"
                     : "=f"(d[0]), "=f"(d[1]), "=f"(d[2]), "=f"(d[3]), "=f"(d[4]), "=f"(d[5]), "=f"(d[6]), "=f"(d[7]),
                       "=f"(d[8]), "=f"(d[9]), "=f"(d[10]), "=f"(d[11]), "=f"(d[12]), "=f"(d[13]), "=f"(d[14]), "=f"(d[15])
                     : "r"(a[0]), "r"(a[1]), "r"(a[2]), "r"(a[3]), "r"(lo), "n"(HI));
    }
}
constexpr uint32_t DESC_H = 64u | (1u << 30);
constexpr uint32_t DESC_G = 16u | (3u << 30);
__device__ __forceinline__ void reg_fence16(float (&d)[16]) {
    asm volatile("" : "+f"(d[0]), "+f"(d[1]), "+f"(d[2]), "+f"(d[3]), "+f"(d[4]), "+f"(d[5]), "+f"(d[6]), "+f"(d[7]),
                      "+f"(d[8]), "+f"(d[9]), "+f"(d[10]), "+f"(d[11]), "+f"(d[12]), "+f"(d[13]), "+f"(d[14]), "+f"(d[15]) :: "memory");
}
__device__ __forceinline__ uint32_t pin(uint32_t x) { return __shfl_sync(0xffffffffu, x, threadIdx.x & 31); }

template <bool FITS>
__device__ __forceinline__ void producer_loop(unsigned char* smem, const __nv_bfloat16* __restrict__ sv, int N, int unit) {
    const uint32_t sbase = smem_u32(smem);
    const uint32_t ubase = __reduce_or_sync(0xffffffffu, sbase + unit * STAGES * STAGE_BYTES);
    const int* misc = reinterpret_cast<const int*>(smem + MS_MISC);
    const int ln = pin(threadIdx.x & 31);
    const int r4 = ln >> 3;
    const unsigned char* gsrc = g_tab + (ln & 7) * 16;
    asm volatile("" : "+l"(gsrc));
    const uint32_t d0 = r4 * 128 + (((ln & 7) ^ r4) << 4);
    const uint32_t goff = ST_G + ln * 32 + (((ln >> 2) & 1) << 4);
    const uint32_t roff = ST_R + ((ln >> 1) & 3) * 16 + (ln >> 3) * 4 + (ln & 1) * 2;
    const unsigned char* ghot = smem + (MS_GH - HOT0 * 32);
    const unsigned char* gcold = reinterpret_cast<const unsigned char*>(g_G);
    asm volatile("" : "+l"(ghot), "+l"(gcold));
    uint32_t sb = ubase, ph = 1;
    const int tv = ln < NQ ? misc[ln] : 0;
    const int total = __reduce_add_sync(0xffffffffu, tv);
    const int s1 = total / 3, s2 = (2 * total) / 3;
    const int un = (int)__reduce_or_sync(0xffffffffu, (uint32_t)unit);
    const int ulo = un == 0 ? 0 : (un == 1 ? s1 : s2);
    const int uhi = un == 0 ? s1 : (un == 1 ? s2 : total);
    const int nnodes = min(NPC, N - (int)blockIdx.x * NPC);
    int gb = 0;
    for (int q = 0; q < NQ; q++) {
        const int gcnt = __reduce_add_sync(0xffffffffu, ln == q ? tv : 0);
        const int ge = gb + gcnt;
        const int beg = gb;
        gb = ge;
        const bool own = beg >= ulo && (beg < uhi || un == 2);
        const int lo = max(beg, ulo), hi = min(ge, uhi);
        if (!own && lo >= hi) continue;
        uint32_t ra = sbase + MS_REC + (lo + ln) * 8;
        const int cnt = hi - beg;
        int rem = max(hi - lo, 0);
        const int lastcap = own ? 24 : 32;
        uint32_t flast = own ? 2u : 4u;
        if (own && un == 0 && beg < s1 && s1 < ge && s1 < s2) flast |= 16u;
        if (own && un < 2 && beg < s2 && s2 < ge) flast |= 32u;
        const unsigned char* svp = reinterpret_cast<const unsigned char*>(sv) +
                                   (size_t)(blockIdx.x * NPC + q * GRP + r4) * 512 + (ln & 7) * 16;
        auto fetch = [&](int left) -> uint2 {
            uint2 r = make_uint2(0, 0);
            if (FITS) {
                asm volatile("ld.shared.v2.u32 {%0,%1}, [%2];" : "=r"(r.x), "=r"(r.y) : "r"(ra));
                ra += 256;
            } else if (ln < left) {
                const int j = cnt - left + ln;
                const int* prq = reinterpret_cast<const int*>(smem + MS_B2) + q * 136;
                int lo = 0, hi = NCTA;
                while (hi - lo > 1) {
                    const int mid = (lo + hi) >> 1;
                    if (prq[mid] <= j) lo = mid; else hi = mid;
                }
                const int b0 = __ldcg(reinterpret_cast<const unsigned short*>(g_pfx + (lo * NCTA + blockIdx.x) * 2) + q + (q >= 7));
                r = __ldcg(g_rec + lo * CH + b0 + (j - prq[lo]));
            }
            return r;
        };
        uint2 rn = fetch(rem);
        bool last;
        do {
            const bool valid = ln < rem;
            last = rem <= lastcap;
            const bool svl = last && own;
            const uint2 r = valid ? rn : make_uint2(0, 0);
            rn = fetch(rem - 32);
            const uint32_t srcv = (r.y >> 16) & 0x7fffu;
            const unsigned char* gq[8];
#pragma unroll
            for (int k = 0; k < 8; k++)
                gq[k] = gsrc + (size_t)__shfl_sync(0xffffffffu, srcv, k * 4 + r4) * ROWB;
            const int lim = rem - r4;
            const int lim6 = svl ? nnodes - q * GRP + 24 - r4 : lim;
            if (svl) { gq[6] = svp; gq[7] = svp + 4 * 512; }
            const uint32_t rxy = hmul2(r.x & 0x9fff9fffu, 0x60806080u);
            const uint32_t rz2 = hmul2(r.y & 0x00009fffu, 0x60806080u);
            const uint32_t qxy = hmul2(rxy, rxy), qz = hmul2(rz2, rz2);
            const float sum = bf16r((__uint_as_float(qxy << 16) + __uint_as_float(qxy & 0xffff0000u)) + __uint_as_float(qz << 16));
            float sq;
            asm("sqrt.approx.ftz.f32 %0, %1;" : "=f"(sq) : "f"(bf16r(sum + 1e-8f)));
            const uint32_t dbits = pack_bf16(0.f, sq);
            float rinv;
            asm("rcp.approx.ftz.f32 %0, %1;" : "=f"(rinv) : "f"(__uint_as_float(dbits)));
            const int di = valid ? max(min((int)(dbits >> 16), DEND - 1) - DBASE, 0) : NTAB - 1;
            const uint4* gp = reinterpret_cast<const uint4*>(di >= HOT0 ? ghot : gcold) + 2 * di;
            const uint4 g0 = gp[0], g1 = gp[1];
            const uint32_t r01 = pack_bf16(__uint_as_float(rxy << 16) * rinv, __uint_as_float(rxy & 0xffff0000u) * rinv);
            const uint32_t r2 = pack_bf16(__uint_as_float(rz2 << 16) * rinv, valid ? 1.0f : 0.f);
            const uint32_t so = ((r.x >> 12) & 6u) | ((r.x >> 26) & 8u);
            const uint32_t fl = last ? (((uint32_t)q << 8) | flast) : 0u;

            const uint32_t bar = sb + ST_CTL;
            mbar_wait(bar + 8, ph);
            const uint32_t dpa = sb + d0, dpb = (dpa ^ 64u) + 512u;
#pragma unroll
            for (int k = 0; k < 8; k++) {
                asm volatile("{\n.reg .pred p;\nsetp.le.s32 p, %2, %3;\n"
                             "cp.async.cg.shared.global [%0], [%1], 16, p;\n"
                             "cp.async.cg.shared.global [%0+4096], [%1+128], 16, p;\n"
                             "cp.async.cg.shared.global [%0+8192], [%1+256], 16, p;\n"
                             "cp.async.cg.shared.global [%0+12288], [%1+384], 16, p;\n}\n"
                             ::"r"(((k & 1) ? dpb : dpa) + (k >> 1) * 1024), "l"(gq[k]), "r"(k < 6 ? lim : lim6), "r"(4 * k) : "memory");
            }
            asm volatile("cp.async.mbarrier.arrive.noinc.shared::cta.b64 [%0];" ::"r"(bar) : "memory");
            const uint32_t za = sb + ST_S + ln * 16;
            asm volatile("st.shared.v4.u32 [%0], {%1,%1,%1,%1};" ::"r"(za), "r"(0u) : "memory");
            asm volatile("st.shared.u16 [%0], %1;" ::"r"(za + so), "h"((unsigned short)(r2 >> 16)) : "memory");
            asm volatile("st.shared.u16 [%0], %1;" ::"r"(sb + roff), "h"((unsigned short)(r01 & 0xffffu)) : "memory");
            asm volatile("st.shared.u16 [%0+64], %1;" ::"r"(sb + roff), "h"((unsigned short)(r01 >> 16)) : "memory");
            asm volatile("st.shared.u16 [%0+128], %1;" ::"r"(sb + roff), "h"((unsigned short)(r2 & 0xffffu)) : "memory");
            asm volatile("st.shared.u32 [%0+16], %1;" ::"r"(bar), "r"(fl) : "memory");
            asm volatile("st.shared.v4.u32 [%0], {%1,%2,%3,%4};" ::"r"(sb + goff),
                         "r"(g0.x), "r"(g0.y), "r"(g0.z), "r"(g0.w) : "memory");
            asm volatile("st.shared.v4.u32 [%0], {%1,%2,%3,%4};" ::"r"((sb + goff) ^ 16u),
                         "r"(g1.x), "r"(g1.y), "r"(g1.z), "r"(g1.w) : "memory");
            asm volatile("fence.proxy.async.shared::cta;" ::: "memory");
            mbar_arrive(bar);
            sb += STAGE_BYTES;
            if (sb == ubase + STAGES * STAGE_BYTES) { sb = ubase; ph ^= 1; }
            rem -= 32;
        } while (!last);
    }
    const uint32_t bar = sb + ST_CTL;
    mbar_wait(bar + 8, ph);
    asm volatile("st.shared.u32 [%0+16], %1;" ::"r"(bar), "r"(8u) : "memory");
    mbar_arrive(bar);
    mbar_arrive(bar);
}

__global__ void __launch_bounds__(M_THREADS, 1)
fused_kernel(const __nv_bfloat16* __restrict__ sv, const __nv_bfloat16* __restrict__ pos,
             const int* __restrict__ src, const int* __restrict__ dst,
             const __nv_bfloat16* __restrict__ freqs, const __nv_bfloat16* __restrict__ w1,
             const __nv_bfloat16* __restrict__ w2, const __nv_bfloat16* __restrict__ wrbf,
             __nv_bfloat16* __restrict__ out, int N, int E) {
    extern __shared__ __align__(1024) unsigned char smem[];
    const int tid = threadIdx.x, lane = tid & 31;
    const int warp = (int)__reduce_or_sync(0xffffffffu, (uint32_t)tid >> 5);
    const uint32_t sbase = smem_u32(smem);
    const uint32_t ghbar = sbase + MS_BAR;
    int* misc = reinterpret_cast<int*>(smem + MS_MISC);
    const bool is_prod = warp >= UNITS * 4;
    const int cta = blockIdx.x;
    const int nnodes = min(NPC, N - cta * NPC);

    STAMP(0, 0);
    const int nquad = max(min(EPC, E - cta * EPC), 0) >> 2;
    for (int i = tid; i < (N * 6 + 15) / 16; i += M_THREADS)
        cp_async16(sbase + PS_POS + i * 16, reinterpret_cast<const unsigned char*>(pos) + i * 16);
    asm volatile("cp.async.commit_group;" ::: "memory");
    int4 es[3], ed[3];
#pragma unroll
    for (int k = 0; k < 3; k++) {
        es[k] = ed[k] = make_int4(0, 0, 0, 0);
        if (tid + k * M_THREADS < nquad) {
            es[k] = __ldcs(reinterpret_cast<const int4*>(src + cta * EPC) + tid + k * M_THREADS);
            ed[k] = __ldcs(reinterpret_cast<const int4*>(dst + cta * EPC) + tid + k * M_THREADS);
        }
    }
    unsigned int epoch;
    asm volatile("ld.relaxed.gpu.global.u32 %0, [%1];" : "=r"(epoch) : "l"(&g_cnt));
    const float freq = __bfloat162float(freqs[tid & 15]);
    if (!is_prod) {
#pragma unroll
        for (int k = 0; k < 2; k++) {
            const int row = (warp & 3) * 8 + k * 4 + (lane >> 3);
            const int node = (warp >> 2) * 32 + row;
            asm volatile("{\n.reg .pred p;\nsetp.ge.s32 p, %2, %3;\n"
                         "cp.async.cg.shared.global [%0], [%1], 16, p;\n"
                         "cp.async.cg.shared.global [%0+4096], [%1+128], 16, p;\n"
                         "cp.async.cg.shared.global [%0+8192], [%1+256], 16, p;\n"
                         "cp.async.cg.shared.global [%0+12288], [%1+384], 16, p;\n}\n"
                         ::"r"(sbase + (warp >> 2) * STAGE_BYTES + row * 128 + (((lane ^ row) & 7) << 4)),
                           "l"(sv + (size_t)(cta * NPC + min(node, nnodes - 1)) * 256 + (lane & 7) * 8), "r"(node), "r"(nnodes) : "memory");
        }
        cp_async16(sbase + PS_WR + (tid / 24) * 400 + (tid % 24) * 16, wrbf + tid * 8);
    }
    {
        const int r = tid >> 3, c = tid & 7;
        cp_async16(sbase + PS_W1 + r * 144 + c * 16, w1 + tid * 8);
        cp_async16(sbase + PS_W2 + r * 272 + c * 16, w2 + r * 192 + c * 8);
        cp_async16(sbase + PS_WV + r * 144 + c * 16, w2 + r * 192 + 64 + c * 8);
        cp_async16(sbase + PS_W2 + r * 272 + 128 + c * 16, w2 + r * 192 + 128 + c * 8);
    }
    asm volatile("cp.async.commit_group;" ::: "memory");
    int* hist = reinterpret_cast<int*>(smem + PS_HIST);
    hist[tid] = 0; hist[tid + 512] = 0; hist[tid + 1024] = 0;
    if (warp == 15) {
        mbar_init(ghbar, 1);
        mbar_init(ghbar + 8, 128);
        mbar_init(ghbar + 16, 128);
        asm volatile("fence.mbarrier_init.release.cluster;" ::: "memory");
    }
    if (warp < 8 && cta * 16 < NTAB) {
        const float d = __uint_as_float((uint32_t)(DBASE + cta * 16 + (tid >> 4)) << 16);
        const float arg = bf16r(d * freq);
        float sn;
        if (fabsf(arg) < 1000.f) {
            const float k = rintf(arg * 0.15915494309189535f);
            sn = __sinf(fmaf(k, 1.7484556000744883e-7f, fmaf(k, -6.2831854820251465f, arg)));
        } else {
            sn = sinf(arg);
        }
        const float rbf = bf16r(__fdividef(bf16r(sn), d));
        const float ca = bf16r(bf16r(3.14159265358979f * d) * 0.2f);
        const float fc = 0.5f * bf16r(bf16r(__cosf(ca)) + 1.0f);
        g_G[cta * 256 + tid] = __float2bfloat16_rn(rbf * fc);
    }
    asm volatile("cp.async.wait_group 1;" ::: "memory");
    __syncthreads();
    STAMP(1, 0);
    {
        uint32_t rx[12], ry[12];
        int key[12];
#pragma unroll
        for (int e = 0; e < 12; e++) {
            const int k = e >> 2, b = e & 3;
            key[e] = -1;
            if (k < 2 || warp * 32 + 2 * M_THREADS < nquad) {
                const uint32_t sn = b == 0 ? es[k].x : b == 1 ? es[k].y : b == 2 ? es[k].z : es[k].w;
                const uint32_t dn = b == 0 ? ed[k].x : b == 1 ? ed[k].y : b == 2 ? ed[k].z : ed[k].w;
                const uint32_t as = sbase + PS_POS + sn * 6, ad = sbase + PS_POS + dn * 6;
                uint32_t sa, sb, da, db;
                asm volatile("ld.shared.u32 %0, [%2];\nld.shared.u32 %1, [%2+4];" : "=r"(sa), "=r"(sb) : "r"(as & ~3u));
                asm volatile("ld.shared.u32 %0, [%2];\nld.shared.u32 %1, [%2+4];" : "=r"(da), "=r"(db) : "r"(ad & ~3u));
                const uint32_t rxy = hsub2(__funnelshift_r(sa, sb, as << 3), __funnelshift_r(da, db, ad << 3));
                const uint32_t rz = hsub2(__funnelshift_r(sb, 0u, as << 3), __funnelshift_r(db, 0u, ad << 3));
                const uint32_t qxy = hmul2(rxy, rxy), qz = hmul2(rz, rz);
                const float sum = (__uint_as_float(qxy << 16) + __uint_as_float(qxy & 0xffff0000u)) + __uint_as_float(qz << 16);
                const uint32_t c = dn / NPC, dl = dn - c * NPC;
                rx[e] = hmul2(rxy, 0x1e801e80u) | ((dl * 0x08002000u) & 0x60006000u);
                ry[e] = __byte_perm(hmul2(rz, 0x1e801e80u), sn, 0x5410) | ((dl * 0x02000200u) & 0x80006000u);
                const int bin = c * NQ + (dl >> 3);
                if (sum < 23.9375f && tid + k * M_THREADS < nquad) key[e] = (bin << 13) | atomicAdd(&hist[bin], 1);
            }
        }
        __syncthreads();
        STAMP(2, 0);
        const int h0 = hist[3 * tid], h1 = hist[3 * tid + 1], h2 = hist[3 * tid + 2];
        int incl = h0 + h1 + h2;
#pragma unroll
        for (int o = 1; o < 32; o <<= 1) {
            const int v = __shfl_up_sync(0xffffffffu, incl, o);
            if (lane >= o) incl += v;
        }
        if (lane == 31) hist[1536 + warp] = incl;
        __syncthreads();
        const int ex = __reduce_add_sync(0xffffffffu, lane < warp ? hist[1536 + lane] : 0) + incl - h2;
        hist[3 * tid] = ex - h1 - h0; hist[3 * tid + 1] = ex - h1; hist[3 * tid + 2] = ex;
        __syncthreads();
        STAMP(3, 0);
        uint2* sorted = reinterpret_cast<uint2*>(smem + PS_POS);
#pragma unroll
        for (int e = 0; e < 12; e++)
            if (key[e] >= 0) sorted[hist[key[e] >> 13] + (key[e] & 8191)] = make_uint2(rx[e], ry[e]);
        asm volatile("cp.async.wait_all;" ::: "memory");
        asm volatile("fence.proxy.async.shared::cta;" ::: "memory");
        __syncthreads();
        STAMP(4, 0);
        const int n16 = (hist[NBIN] + 1) >> 1;
#pragma unroll
        for (int k = 0; k < 5; k++)
            if (tid + k * M_THREADS < n16)
                reinterpret_cast<uint4*>(g_rec + cta * CH)[tid + k * M_THREADS] =
                    reinterpret_cast<const uint4*>(smem + PS_POS)[tid + k * M_THREADS];
        __syncthreads();
        STAMP(5, 0);
    }
    epoch /= NCTA;
    const int g = lane >> 2, t = lane & 3;
    unsigned short* pf = reinterpret_cast<unsigned short*>(smem + PS_PF);
    int* b2 = reinterpret_cast<int*>(smem + MS_B2);
    if (is_prod) {
        const uint32_t tag = ((epoch + 1) & 0xffffu) << 16;
        const int pt = tid - UNITS * 128, pw = warp - UNITS * 4;
        __threadfence();
        for (int c = pt; c < NCTA; c += 128) {
            const int* h = hist + c * NQ;
            asm volatile("st.relaxed.gpu.global.v4.u32 [%0], {%1,%2,%3,%4};" ::"l"(g_pfx + (cta * NCTA + c) * 2),
                         "r"(h[0] | (h[1] << 16)), "r"(h[2] | (h[3] << 16)), "r"(h[4] | (h[5] << 16)), "r"(h[6] | tag) : "memory");
            asm volatile("st.relaxed.gpu.global.v4.u32 [%0], {%1,%2,%3,%4};" ::"l"(g_pfx + (cta * NCTA + c) * 2 + 1),
                         "r"(h[7] | (h[8] << 16)), "r"(h[9] | (h[10] << 16)), "r"(0), "r"(tag) : "memory");
        }
        STAMP(6, 384);
        if (pt < UNITS * STAGES) {
            mbar_init(sbase + pt * STAGE_BYTES + ST_CTL, 64);
            mbar_init(sbase + pt * STAGE_BYTES + ST_CTL + 8, 4);
            asm volatile("fence.mbarrier_init.release.cluster;" ::: "memory");
        }
        for (int p = pt; p < NCTA; p += 128) {
            const uint4* bp = g_pfx + (p * NCTA + cta) * 2;
            uint4 b0, b1;
            int spin = 0;
            do {
                asm volatile("ld.relaxed.gpu.global.v4.u32 {%0,%1,%2,%3}, [%4];" : "=r"(b0.x), "=r"(b0.y), "=r"(b0.z), "=r"(b0.w) : "l"(bp) : "memory");
                asm volatile("ld.relaxed.gpu.global.v4.u32 {%0,%1,%2,%3}, [%4];" : "=r"(b1.x), "=r"(b1.y), "=r"(b1.z), "=r"(b1.w) : "l"(bp + 1) : "memory");
            } while ((((b0.w ^ tag) | (b1.w ^ tag)) & 0xffff0000u) && ++spin < (1 << 22));
            reinterpret_cast<uint4*>(pf)[p * 2] = make_uint4(b0.x, b0.y, b0.z, __byte_perm(b0.w, b1.x, 0x5410));
            reinterpret_cast<uint2*>(pf)[p * 4 + 2] = make_uint2(__byte_perm(b1.x, b1.y, 0x5432), b1.y >> 16);
        }
        asm volatile("fence.acq_rel.gpu;" ::: "memory");
        asm volatile("bar.sync 4, 128;" ::: "memory");
        STAMP(7, 384);
#pragma unroll 11
        for (int p = pw; p < NCTA; p += 4) {
            const int i = (pf[p * 16] & ~1) + 2 * lane;
            if (i < pf[p * 16 + NQ])
                cp_async16(sbase + (3 + (p >> 5)) * STAGE_BYTES + (p & 31) * 512 + lane * 16, g_rec + p * CH + i);
        }
        for (int i = pt; i < (NTAB - HOT0) * 2; i += 128) cp_async16(sbase + MS_GH + i * 16, g_G + HOT0 * NRBF + i * 8);
#pragma unroll 1
        for (int q = pw; q < NQ; q += 4) {
            int lo[5], cq[5], sum = 0;
#pragma unroll
            for (int k = 0; k < 5; k++) {
                const int p = min(lane * 5 + k, NCTA - 1);
                lo[k] = pf[p * 16 + q];
                cq[k] = lane * 5 + k < NCTA ? pf[p * 16 + q + 1] - lo[k] : 0;
                sum += cq[k];
            }
            int in2 = sum;
#pragma unroll
            for (int o = 1; o < 32; o <<= 1) {
                const int v = __shfl_up_sync(0xffffffffu, in2, o);
                if (lane >= o) in2 += v;
            }
            int pre = in2 - sum;
            if (lane == 31) misc[q] = in2;
#pragma unroll
            for (int k = 0; k < 5; k++) {
                if (lane * 5 + k < NCTA) b2[q * 136 + lane * 5 + k] = pre;
                pre += cq[k];
            }
        }
        asm volatile("cp.async.wait_all;" ::: "memory");
        STAMP(10, 384);
    } else {
        const int w = warp & 3;
        const uint32_t tb = sbase + (warp >> 2) * STAGE_BYTES;
        const int krow = (lane & 7) + 8 * (lane >> 4), mcol = 2 * w + ((lane >> 3) & 1);
        const uint32_t ta = tb + krow * 128 + ((uint32_t)(mcol ^ (lane & 7)) << 4);
        const uint32_t dh = (tb >> 4) | (1u << 16);
        uint32_t a[4][4];
        float d[16];
#pragma unroll
        for (int q = 0; q < 4; q++) ldsm4t(a[q], sbase + PS_W1 + (16 * q + krow) * 144 + mcol * 16);
        asm volatile("wgmma.fence.sync.aligned;" ::: "memory");
        wgmma_n32<0, DESC_H>(d, a[0], dh);
        wgmma_n32<1, DESC_H>(d, a[1], dh + 2);
        wgmma_n32<1, DESC_H>(d, a[2], dh + 4);
        wgmma_n32<1, DESC_H>(d, a[3], dh + 6);
        asm volatile("wgmma.commit_group.sync.aligned;" ::: "memory");
        asm volatile("wgmma.wait_group.sync.aligned 0;" ::: "memory");
        reg_fence16(d);
#pragma unroll
        for (int q = 0; q < 4; q++) ldsm4t(a[q], sbase + PS_WV + (16 * q + krow) * 144 + mcol * 16);
        uint32_t x[2][4];
#pragma unroll
        for (int i = 0; i < 8; i++) {
            const uint32_t z = pack_bf16(d[2 * i], d[2 * i + 1]);
            const float z0 = __uint_as_float(z << 16), z1 = __uint_as_float(z & 0xffff0000u);
            x[i >> 2][i & 3] = pack_bf16(__fdividef(z0, 1.0f + __expf(-z0)), __fdividef(z1, 1.0f + __expf(-z1)));
        }
        asm volatile("bar.sync %0, 128;" ::"r"(1 + (warp >> 2)) : "memory");
        stsm4t(ta, x[0]);
        stsm4t(ta + 2048, x[1]);
        asm volatile("fence.proxy.async.shared::cta;" ::: "memory");
        asm volatile("bar.sync %0, 128;" ::"r"(1 + (warp >> 2)) : "memory");
        STAMP(14, 0);
        asm volatile("wgmma.fence.sync.aligned;" ::: "memory");
        wgmma_n32<0, DESC_H>(d, a[0], dh);
        wgmma_n32<1, DESC_H>(d, a[1], dh + 2);
        wgmma_n32<1, DESC_H>(d, a[2], dh + 4);
        wgmma_n32<1, DESC_H>(d, a[3], dh + 6);
        asm volatile("wgmma.commit_group.sync.aligned;" ::: "memory");
        asm volatile("wgmma.wait_group.sync.aligned 0;" ::: "memory");
        reg_fence16(d);
#pragma unroll
        for (int i = 0; i < 8; i++) x[i >> 2][i & 3] = pack_bf16(d[2 * i], d[2 * i + 1]);
#pragma unroll
        for (int j = 1; j < 4; j++)
#pragma unroll
            for (int s = 0; s < 2; s++) {
                uint32_t v[4];
                ldsm4t(v, ta + j * 4096 + s * 2048);
#pragma unroll
                for (int e = 0; e < 4; e++) v[e] = hmul2(v[e], x[s][e]);
                stsm4t(ta + j * 4096 + s * 2048, v);
            }
        asm volatile("bar.sync %0, 128;" ::"r"(1 + (warp >> 2)) : "memory");
        STAMP(15, 0);
#pragma unroll
        for (int k = 0; k < 2; k++) {
            const int row = w * 8 + k * 4 + (lane >> 3);
            const int node = (warp >> 2) * 32 + row;
            if (node < nnodes) {
                uint4* o = reinterpret_cast<uint4*>(g_tab + (size_t)(cta * NPC + node) * ROWB) + (lane & 7);
                const unsigned char* ip = smem + (warp >> 2) * STAGE_BYTES + row * 128 + (((lane ^ row) & 7) << 4);
#pragma unroll
                for (int c = 0; c < 4; c++) o[c * 8] = *reinterpret_cast<const uint4*>(ip + c * 4096);
            }
        }
        STAMP(8, 0);
        asm volatile("bar.sync 5, 384;" ::: "memory");
        if (warp == 0) {
            __threadfence();
            if (lane == 0) atomicInc(&g_cnt, NCTA * 65536u - 1);
        }
        STAMP(9, 0);
    }
    __syncthreads();
    STAMP(11, 0);
    {
        int gbase = lane < NQ ? misc[lane] : 0;
#pragma unroll
        for (int o = 1; o < 16; o <<= 1) {
            const int v = __shfl_up_sync(0xffffffffu, gbase, o);
            if (lane >= o) gbase += v;
        }
        const bool fits = __reduce_max_sync(0xffffffffu, gbase) <= RCAP;
        gbase = __shfl_up_sync(0xffffffffu, gbase, 1);
        if (lane == 0) gbase = 0;
        if (fits) {
            uint2* srec = reinterpret_cast<uint2*>(smem + MS_REC);
            bool more = false;
#pragma unroll
            for (int k = 0; k < 9; k++) {
                const int p = min(warp + 16 * k, NCTA - 1);
                const int beg = pf[p * 16], end = warp + 16 * k < NCTA ? pf[p * 16 + NQ] : 0;
                const uint2 v = reinterpret_cast<const uint2*>(smem + (3 + (p >> 5)) * STAGE_BYTES + (p & 31) * 512)[(beg & 1) + lane];
                const int q = min((int)(((v.x >> 30) & 1u) | ((v.y >> 12) & 6u) | ((v.y >> 28) & 8u)), NQ - 1);
                const int o = __shfl_sync(0xffffffffu, gbase, q) + b2[q * 136 + p] - pf[p * 16 + q];
                if (beg + lane < end) srec[o + beg + lane] = v;
                more |= beg + 32 < end;
            }
            if (more) {
#pragma unroll 1
                for (int p = warp; p < NCTA; p += 16) {
                    const int beg = pf[p * 16], end = pf[p * 16 + NQ];
                    const uint2* raw = reinterpret_cast<const uint2*>(smem + (3 + (p >> 5)) * STAGE_BYTES + (p & 31) * 512);
#pragma unroll 1
                    for (int i0 = beg + 32; i0 < end; i0 += 32) {
                        const int i = i0 + lane, o = i - (beg & ~1);
                        uint2 v = make_uint2(0, 0);
                        if (i < end) v = o < 64 ? raw[o] : __ldcg(g_rec + p * CH + i);
                        const int q = (int)(((v.x >> 30) & 1u) | ((v.y >> 12) & 6u) | ((v.y >> 28) & 8u));
                        const int gb = __shfl_sync(0xffffffffu, gbase, q);
                        if (i < end) srec[gb + b2[q * 136 + p] - pf[p * 16 + q] + i] = v;
                    }
                }
            }
        }
        __syncthreads();
    }
    STAMP(12, 0);

    if (is_prod) {
        asm volatile("setmaxnreg.dec.sync.aligned.u32 80;");
        const int unit = warp - UNITS * 4;
        if (unit < UNITS) {
            {
                const unsigned int ep = __reduce_or_sync(0xffffffffu, epoch);
                unsigned int c;
                int spin = 0;
                do {
                    asm volatile("ld.acquire.gpu.global.u32 %0, [%1];" : "=r"(c) : "l"(&g_cnt) : "memory");
                    c = __reduce_or_sync(0xffffffffu, c);
                } while (c / NCTA == ep && ++spin < (1 << 22));
            }
            STAMP(13, 384);
            asm volatile("bar.sync 6, 480;" ::: "memory");
            STAMP(21, 384);
            if (__reduce_add_sync(0xffffffffu, lane < NQ ? misc[lane] : 0) <= RCAP) producer_loop<true>(smem, sv, N, unit);
            else producer_loop<false>(smem, sv, N, unit);
            STAMP(22 + unit, 384 + 32 * unit);
        }
    } else {
        asm volatile("setmaxnreg.inc.sync.aligned.u32 144;");
        const int unit = warp >> 2, w = warp & 3;
        const uint32_t ubase = sbase + unit * STAGES * STAGE_BYTES;
        uint32_t wa[3][4], pa[2][4][4];
        {
            const int krow = (lane & 7) + 8 * (lane >> 4), mcol = 2 * w + ((lane >> 3) & 1);
#pragma unroll
            for (int q = 0; q < 4; q++) {
                ldsm4t(pa[0][q], sbase + PS_W2 + (16 * q + krow) * 272 + mcol * 16);
                ldsm4t(pa[1][q], sbase + PS_W2 + (16 * q + krow) * 272 + 128 + mcol * 16);
            }
#pragma unroll
            for (int p = 0; p < 3; p++) ldsm4t(wa[p], sbase + PS_WR + krow * 400 + p * 128 + mcol * 16);
            asm volatile("bar.arrive 6, 480;" ::: "memory");
        }
        float acc[4][4];
#pragma unroll
        for (int c = 0; c < 4; c++)
#pragma unroll
            for (int e = 0; e < 4; e++) acc[c][e] = 0.f;
        const int erow = (lane & 7) + 8 * (lane >> 4);
        const int ehalf = (lane >> 3) & 1;
        const uint32_t ua = pin(4096 + erow * 128 + ((uint32_t)((2 * w + ehalf) ^ (lane & 7)) << 4));
        const uint32_t sa = pin(ST_S + lane * 16);
        const uint32_t ra = pin(ST_R + t * 16);
        const uint32_t ub = __reduce_or_sync(0xffffffffu, ubase);
        uint32_t sb = ub;
        uint32_t ph = 0;
        const bool elected = sa == ST_S;
        while (true) {
            mbar_wait(sb + ST_CTL, ph);
            {
                const uint32_t dh = (sb >> 4) | (1u << 16);
                const uint32_t dg = dh + (ST_G >> 4);
                uint32_t m[2][4], wv[2][4], u[3][4], sf[4], rr[3][2];
                float p0[16], f0[16], fv[16];
                asm volatile("wgmma.fence.sync.aligned;" ::: "memory");
                wgmma_n32<0, DESC_G>(f0, wa[2], dg);
                wgmma_n32<0, DESC_H>(p0, pa[1][0], dh);
                wgmma_n32<1, DESC_H>(p0, pa[1][1], dh + 2);
                wgmma_n32<1, DESC_H>(p0, pa[1][2], dh + 4);
                wgmma_n32<1, DESC_H>(p0, pa[1][3], dh + 6);
                wgmma_n32<0, DESC_G>(fv, wa[1], dg);
                asm volatile("wgmma.commit_group.sync.aligned;" ::: "memory");
#pragma unroll
                for (int j = 0; j < 3; j++) {
                    ldsm4t(u[j], sb + ua + j * 4096);
                    asm volatile("ld.shared.v2.u32 {%0,%1}, [%2];" : "=r"(rr[j][0]), "=r"(rr[j][1]) : "r"(sb + ra + j * 64));
                }
                ldsm4t(sf, sb + sa);
                asm volatile("wgmma.wait_group.sync.aligned 0;" ::: "memory");
                reg_fence16(fv); reg_fence16(f0); reg_fence16(p0);
#pragma unroll
                for (int i = 0; i < 8; i++) {
                    m[i >> 2][i & 3] = pack_bf16(f0[2 * i] * p0[2 * i], f0[2 * i + 1] * p0[2 * i + 1]);
                    wv[i >> 2][i & 3] = pack_bf16(fv[2 * i], fv[2 * i + 1]);
                }
                asm volatile("wgmma.fence.sync.aligned;" ::: "memory");
                wgmma_n32<0, DESC_G>(f0, wa[0], dg);
                wgmma_n32<0, DESC_H>(p0, pa[0][0], dh);
                wgmma_n32<1, DESC_H>(p0, pa[0][1], dh + 2);
                wgmma_n32<1, DESC_H>(p0, pa[0][2], dh + 4);
                wgmma_n32<1, DESC_H>(p0, pa[0][3], dh + 6);
                asm volatile("wgmma.commit_group.sync.aligned;" ::: "memory");
                uint32_t v1[3][4];
#pragma unroll
                for (int j = 0; j < 3; j++)
#pragma unroll
                    for (int e = 0; e < 4; e++) u[j][e] = hfma2(m[0][e], rr[j][e >> 1], hmul2(u[j][e], wv[0][e]));
#pragma unroll
                for (int j = 0; j < 3; j++) {
                    ldsm4t(v1[j], sb + ua + j * 4096 + 2048);
                    asm volatile("ld.shared.v2.u32 {%0,%1}, [%2];" : "=r"(rr[j][0]), "=r"(rr[j][1]) : "r"(sb + ra + j * 64 + 8));
                }
#pragma unroll
                for (int j = 0; j < 3; j++)
#pragma unroll
                    for (int e = 0; e < 4; e++) v1[j][e] = hfma2(m[1][e], rr[j][e >> 1], hmul2(v1[j][e], wv[1][e]));
#pragma unroll
                for (int j = 0; j < 3; j++) mma16816(acc[j + 1], u[j], sf[0], sf[1]);
#pragma unroll
                for (int j = 0; j < 3; j++) mma16816(acc[j + 1], v1[j], sf[2], sf[3]);
                asm volatile("wgmma.wait_group.sync.aligned 0;" ::: "memory");
                reg_fence16(f0); reg_fence16(p0);
#pragma unroll
                for (int i = 0; i < 8; i++)
                    m[i >> 2][i & 3] = pack_bf16(f0[2 * i] * p0[2 * i], f0[2 * i + 1] * p0[2 * i + 1]);
                mma16816(acc[0], m[0], sf[0], sf[1]);
                mma16816(acc[0], m[1], sf[2], sf[3]);
            }
            uint32_t flags;
            asm volatile("ld.shared.u32 %0, [%1+16];" : "=r"(flags) : "r"(sb + ST_CTL));
            if (flags) {
                if (flags & 8u) break;
                float* part = reinterpret_cast<float*>(smem + MS_PART) + (tid & 127);
                if (flags & 4u) {
#pragma unroll
                    for (int i = 0; i < 16; i++) part[(unit - 1) * 2048 + i * 128] = acc[i >> 2][i & 3];
                    mbar_arrive(sbase + MS_BAR + unit * 8);
                } else {
#pragma unroll 1
                    for (int k = 0; k < 2; k++) {
                        if (flags & (16u << k)) {
                            mbar_wait(sbase + MS_BAR + 8 + k * 8, 0);
#pragma unroll
                            for (int i = 0; i < 16; i++) acc[i >> 2][i & 3] += part[k * 2048 + i * 128];
                        }
                    }
                    const uint32_t ea = sb + (lane >> 4) * 4096 + (24 + (lane & 7)) * 128 +
                                        ((uint32_t)((2 * w + ((lane >> 3) & 1)) ^ (lane & 7)) << 4);
#pragma unroll
                    for (int k = 0; k < 2; k++) {
                        uint32_t v[4];
                        ldsm4t(v, ea + k * 8192);
#pragma unroll
                        for (int e = 0; e < 4; e++)
                            v[e] = pack_bf16(__uint_as_float(v[e] << 16) + acc[2 * k + (e >> 1)][2 * (e & 1)],
                                             __uint_as_float(v[e] & 0xffff0000u) + acc[2 * k + (e >> 1)][2 * (e & 1) + 1]);
                        stsm4t(ea + k * 8192, v);
                    }
                    __syncwarp();
                    const int ln0 = (int)(flags >> 8) * GRP + (lane >> 2);
                    const int c0 = (lane >> 1) & 1, ch = 2 * w + (lane & 1);
                    uint4* op = reinterpret_cast<uint4*>(out + (size_t)(blockIdx.x * NPC + ln0) * 256) + c0 * 8 + ch;
                    const uint32_t ia = sb + c0 * 4096 + (24 + (lane >> 2)) * 128 + ((uint32_t)(ch ^ (lane >> 2)) << 4);
#pragma unroll
                    for (int k = 0; k < 2; k++) {
                        asm volatile("{\n.reg .pred p;\n.reg .b32 a, b, c, d;\nsetp.lt.s32 p, %2, %3;\n"
                                     "ld.shared.v4.u32 {a, b, c, d}, [%0];\n"
                                     "@p st.global.v4.u32 [%1], {a, b, c, d};\n}\n"
                                     ::"r"(ia + k * 8192), "l"(op + k * 16), "r"(ln0), "r"(min(NPC, N - (int)blockIdx.x * NPC)) : "memory");
                    }
                }
#pragma unroll
                for (int i = 0; i < 16; i++) acc[i >> 2][i & 3] = 0.f;
            }
            __syncwarp();
            if (elected) mbar_arrive(sb + ST_CTL + 8);
            sb += STAGE_BYTES;
            if (sb == ub + STAGES * STAGE_BYTES) { sb = ub; ph ^= 1; }
        }
        STAMP(26 + unit, 128 * unit);
    }
}

}

extern "C" void kernel_launch(void* const* d_in, const int* in_sizes, int n_in, void* d_out, int out_size) {
    const __nv_bfloat16* sv = (const __nv_bfloat16*)d_in[0];
    const __nv_bfloat16* pos = (const __nv_bfloat16*)d_in[1];
    const int* src = (const int*)d_in[2];
    const int* dst = (const int*)d_in[3];
    const __nv_bfloat16* freqs = (const __nv_bfloat16*)d_in[4];
    const __nv_bfloat16* w1 = (const __nv_bfloat16*)d_in[5];
    const __nv_bfloat16* w2 = (const __nv_bfloat16*)d_in[6];
    const __nv_bfloat16* wrbf = (const __nv_bfloat16*)d_in[7];
    __nv_bfloat16* out = (__nv_bfloat16*)d_out;
    const int N = in_sizes[1] / 3;
    const int E = in_sizes[2];

    static bool init = false;
    if (!init) {
        cudaFuncSetAttribute(fused_kernel, cudaFuncAttributeMaxDynamicSharedMemorySize, M_SMEM);
        init = true;
    }
    fused_kernel<<<NCTA, M_THREADS, M_SMEM, cudaStreamPerThread>>>(sv, pos, src, dst, freqs, w1, w2, wrbf, out, N, E);
}
```

```cpp
#include <cuda_runtime.h>
#include <cuda_bf16.h>
#include <stdint.h>

namespace {

constexpr int D = 64;
constexpr int NRBF = 16;
constexpr int MAXN = 10000;
constexpr int MAXE = 640000;
constexpr int NCTA = 132;
constexpr int GRP = 8;
constexpr int NPC = (MAXN + NCTA - 1) / NCTA;
constexpr int NQ = (NPC + GRP - 1) / GRP;
constexpr int NBIN = NCTA * NQ;
constexpr int CH = 4864;
constexpr int DBASE = 0x38C0;
constexpr int DEND = 0x40A0;
constexpr int NTAB = DEND - DBASE;
constexpr int ROWB = 512;

__device__ __align__(128) unsigned char g_tab[(size_t)(MAXN + 16) * ROWB];
__device__ __align__(128) __nv_bfloat16 g_G[NTAB * NRBF];
__device__ __align__(128) uint2 g_rec[NCTA * CH];
__device__ __align__(128) uint4 g_pfx[NCTA * NCTA * 2];
__device__ unsigned int g_cnt;

#define STAMP(k, tt) do {} while (0)

__device__ __forceinline__ uint32_t smem_u32(const void* p) { return (uint32_t)__cvta_generic_to_shared(p); }
__device__ __forceinline__ uint32_t pack_bf16(float lo, float hi) {
    uint32_t r;
    asm("cvt.rn.bf16x2.f32 %0, %1, %2;" : "=r"(r) : "f"(hi), "f"(lo));
    return r;
}
__device__ __forceinline__ float bf16r(float x) { return __uint_as_float(pack_bf16(0.f, x) & 0xffff0000u); }
__device__ __forceinline__ uint32_t hmul2(uint32_t a, uint32_t b) {
    uint32_t r;
    asm("mul.rn.bf16x2 %0, %1, %2;" : "=r"(r) : "r"(a), "r"(b));
    return r;
}
__device__ __forceinline__ uint32_t hsub2(uint32_t a, uint32_t b) {
    uint32_t r;
    asm("sub.rn.bf16x2 %0, %1, %2;" : "=r"(r) : "r"(a), "r"(b));
    return r;
}
__device__ __forceinline__ uint32_t hfma2(uint32_t a, uint32_t b, uint32_t c) {
    uint32_t r;
    asm("fma.rn.bf16x2 %0, %1, %2, %3;" : "=r"(r) : "r"(a), "r"(b), "r"(c));
    return r;
}
__device__ __forceinline__ void mma16816(float (&c)[4], const uint32_t (&a)[4], uint32_t b0, uint32_t b1) {
    asm volatile("mma.sync.aligned.m16n8k16.row.col.f32.bf16.bf16.f32 {%0,%1,%2,%3}, {%4,%5,%6,%7}, {%8,%9}, {%0,%1,%2,%3};"
                 : "+f"(c[0]), "+f"(c[1]), "+f"(c[2]), "+f"(c[3])
                 : "r"(a[0]), "r"(a[1]), "r"(a[2]), "r"(a[3]), "r"(b0), "r"(b1));
}
__device__ __forceinline__ void mma16816_z(float (&c)[4], const uint32_t (&a)[4], uint32_t b0, uint32_t b1) {
    asm volatile("mma.sync.aligned.m16n8k16.row.col.f32.bf16.bf16.f32 {%0,%1,%2,%3}, {%4,%5,%6,%7}, {%8,%9}, {%10,%10,%10,%10};"
                 : "=f"(c[0]), "=f"(c[1]), "=f"(c[2]), "=f"(c[3])
                 : "r"(a[0]), "r"(a[1]), "r"(a[2]), "r"(a[3]), "r"(b0), "r"(b1), "f"(0.f));
}
__device__ __forceinline__ void ldsm4(uint32_t (&r)[4], uint32_t addr) {
    asm volatile("ldmatrix.sync.aligned.m8n8.x4.shared.b16 {%0,%1,%2,%3}, [%4];"
                 : "=r"(r[0]), "=r"(r[1]), "=r"(r[2]), "=r"(r[3]) : "r"(addr));
}
__device__ __forceinline__ void ldsm4t(uint32_t (&r)[4], uint32_t addr) {
    asm volatile("ldmatrix.sync.aligned.m8n8.x4.trans.shared.b16 {%0,%1,%2,%3}, [%4];"
                 : "=r"(r[0]), "=r"(r[1]), "=r"(r[2]), "=r"(r[3]) : "r"(addr));
}
__device__ __forceinline__ void stsm4t(uint32_t addr, const uint32_t (&r)[4]) {
    asm volatile("stmatrix.sync.aligned.m8n8.x4.trans.shared.b16 [%0], {%1,%2,%3,%4};"
                 ::"r"(addr), "r"(r[0]), "r"(r[1]), "r"(r[2]), "r"(r[3]) : "memory");
}
__device__ __forceinline__ void cp_async16(uint32_t dst, const void* src) {
    asm volatile("cp.async.cg.shared.global [%0], [%1], 16;" ::"r"(dst), "l"(src) : "memory");
}
__device__ __forceinline__ void mbar_init(uint32_t bar, int cnt) {
    asm volatile("mbarrier.init.shared::cta.b64 [%0], %1;" ::"r"(bar), "r"(cnt) : "memory");
}
__device__ __forceinline__ void mbar_arrive(uint32_t bar) {
    asm volatile("mbarrier.arrive.shared::cta.b64 _, [%0];" ::"r"(bar) : "memory");
}
__device__ __forceinline__ void mbar_expect_tx(uint32_t bar, uint32_t bytes) {
    asm volatile("mbarrier.arrive.expect_tx.shared::cta.b64 _, [%0], %1;" ::"r"(bar), "r"(bytes) : "memory");
}
__device__ __forceinline__ void mbar_wait(uint32_t bar, uint32_t parity) {
    asm volatile(
        "{\n.reg .pred p;\n.reg .u32 n;\nmov.u32 n, 0;\n"
        "WAIT_%=:\n"
        "mbarrier.try_wait.parity.shared::cta.b64 p, [%0], %1, %2;\n"
        "@p bra DONE_%=;\n"
        "add.u32 n, n, 1;\n"
        "setp.lt.u32 p, n, 100000;\n"
        "@p bra WAIT_%=;\n"
        "exit;\n"
        "DONE_%=:\n}\n" ::"r"(bar), "r"(parity), "r"(10000u) : "memory");
}
__device__ __forceinline__ void bulk_g2s(uint32_t dst, const void* src, uint32_t bytes, uint32_t bar) {
    asm volatile("cp.async.bulk.shared::cluster.global.mbarrier::complete_tx::bytes [%0], [%1], %2, [%3];"
                 ::"r"(dst), "l"(src), "r"(bytes), "r"(bar) : "memory");
}
__device__ __forceinline__ void bulk_s2g(void* dst, uint32_t src, uint32_t bytes) {
    asm volatile("cp.async.bulk.global.shared::cta.bulk_group [%0], [%1], %2;" ::"l"(dst), "r"(src), "r"(bytes) : "memory");
}

constexpr int UNITS = 3;
constexpr int STAGES = 3;
constexpr int M_THREADS = UNITS * 128 + 128;
constexpr int ST_G = 4 * 4096;
constexpr int ST_S = ST_G + 1024;
constexpr int ST_R = ST_S + 512;
constexpr int ST_CTL = ST_R + 192;
constexpr int STAGE_BYTES = ST_S + 1024;
constexpr int RCAP = 3904;
constexpr int HOT0 = 0x3F00 - DBASE;
constexpr int MS_REC = UNITS * STAGES * STAGE_BYTES;
constexpr int MS_PART = MS_REC + RCAP * 8;
constexpr int MS_GH = MS_PART + 2 * 8192;
constexpr int MS_B2 = MS_GH + (NTAB - HOT0) * 32;
constexpr int MS_MISC = MS_B2 + NQ * 136 * 4;
constexpr int MS_BAR = MS_MISC + 32 * 4;
constexpr int M_SMEM = MS_BAR + 64;
constexpr int EPC = 4852;
constexpr int PS_POS = UNITS * STAGE_BYTES;
constexpr int PS_WR = 7 * STAGE_BYTES + 4096;
constexpr int PS_PF = 7 * STAGE_BYTES + 12288;
constexpr int PS_W2 = 8 * STAGE_BYTES;
constexpr int PS_W1 = MS_REC;
constexpr int PS_WV = PS_W1 + 64 * 144;
constexpr int PS_HIST = PS_WV + 64 * 144;
static_assert(PS_POS + 60032 <= 7 * STAGE_BYTES && PS_HIST + (1536 + 32) * 4 <= MS_PART && 64 * 272 <= ST_CTL &&
              EPC * NCTA >= MAXE && EPC <= CH && CH * 8 <= 60032, "phase-1 layout");
static_assert(M_SMEM <= 232448, "smem");
static_assert(MS_BAR % 8 == 0 && MS_GH % 16 == 0 && STAGE_BYTES % 1024 == 0, "align");

template <int ACC, uint32_t HI>
__device__ __forceinline__ void wgmma_n32(float (&d)[16], const uint32_t (&a)[4], uint32_t lo) {
    if (ACC) {
        asm volatile("{\n.reg .b64 dd;\nmov.b64 dd, {%20, %21};\n"
                     "wgmma.mma_async.sync.aligned.m64n32k16.f32.bf16.bf16 {%0,%1,%2,%3,%4,%5,%6,%7,%8,%9,%10,%11,%12,%13,%14,%15}, {%16,%17,%18,%19}, dd, 1, 1, 1, 0;\n}\n"
                     : "+f"(d[0]), "+f"(d[1]), "+f"(d[2]), "+f"(d[3]), "+f"(d[4]), "+f"(d[5]), "+f"(d[6]), "+f"(d[7]),
                       "+f"(d[8]), "+f"(d[9]), "+f"(d[10]), "+f"(d[11]), "+f"(d[12]), "+f"(d[13]), "+f"(d[14]), "+f"(d[15])
                     : "r"(a[0]), "r"(a[1]), "r"(a[2]), "r"(a[3]), "r"(lo), "n"(HI));
    } else {
        asm volatile("{\n.reg .b64 dd;\nmov.b64 dd, {%20, %21};\n"
                     "wgmma.mma_async.sync.aligned.m64n32k16.f32.bf16.bf16 {%0,%1,%2,%3,%4,%5,%6,%7,%8,%9,%10,%11,%12,%13,%14,%15}, {%16,%17,%18,%19}, dd, 0, 1, 1, 0;\n}\n"
                     : "=f"(d[0]), "=f"(d[1]), "=f"(d[2]), "=f"(d[3]), "=f"(d[4]), "=f"(d[5]), "=f"(d[6]), "=f"(d[7]),
                       "=f"(d[8]), "=f"(d[9]), "=f"(d[10]), "=f"(d[11]), "=f"(d[12]), "=f"(d[13]), "=f"(d[14]), "=f"(d[15])
                     : "r"(a[0]), "r"(a[1]), "r"(a[2]), "r"(a[3]), "r"(lo), "n"(HI));
    }
}
constexpr uint32_t DESC_H = 64u | (1u << 30);
constexpr uint32_t DESC_G = 16u | (3u << 30);
__device__ __forceinline__ void reg_fence16(float (&d)[16]) {
    asm volatile("" : "+f"(d[0]), "+f"(d[1]), "+f"(d[2]), "+f"(d[3]), "+f"(d[4]), "+f"(d[5]), "+f"(d[6]), "+f"(d[7]),
                      "+f"(d[8]), "+f"(d[9]), "+f"(d[10]), "+f"(d[11]), "+f"(d[12]), "+f"(d[13]), "+f"(d[14]), "+f"(d[15]) :: "memory");
}
__device__ __forceinline__ uint32_t pin(uint32_t x) { return __shfl_sync(0xffffffffu, x, threadIdx.x & 31); }

template <bool FITS>
__device__ __forceinline__ void producer_loop(unsigned char* smem, const __nv_bfloat16* __restrict__ sv, int N, int unit) {
    const uint32_t sbase = smem_u32(smem);
    const uint32_t ubase = __reduce_or_sync(0xffffffffu, sbase + unit * STAGES * STAGE_BYTES);
    const int* misc = reinterpret_cast<const int*>(smem + MS_MISC);
    const int ln = pin(threadIdx.x & 31);
    const int r4 = ln >> 3;
    const unsigned char* gsrc = g_tab + (ln & 7) * 16;
    asm volatile("" : "+l"(gsrc));
    const uint32_t d0 = r4 * 128 + (((ln & 7) ^ r4) << 4);
    const uint32_t goff = ST_G + ln * 32 + (((ln >> 2) & 1) << 4);
    const uint32_t roff = ST_R + ((ln >> 1) & 3) * 16 + (ln >> 3) * 4 + (ln & 1) * 2;
    const unsigned char* ghot = smem + (MS_GH - HOT0 * 32);
    const unsigned char* gcold = reinterpret_cast<const unsigned char*>(g_G);
    asm volatile("" : "+l"(ghot), "+l"(gcold));
    uint32_t sb = ubase, ph = 1;
    const int tv = ln < NQ ? misc[ln] : 0;
    const int total = __reduce_add_sync(0xffffffffu, tv);
    const int s1 = total / 3, s2 = (2 * total) / 3;
    const int un = (int)__reduce_or_sync(0xffffffffu, (uint32_t)unit);
    const int ulo = un == 0 ? 0 : (un == 1 ? s1 : s2);
    const int uhi = un == 0 ? s1 : (un == 1 ? s2 : total);
    const int nnodes = min(NPC, N - (int)blockIdx.x * NPC);
    int gb = 0;
    for (int q = 0; q < NQ; q++) {
        const int gcnt = __reduce_add_sync(0xffffffffu, ln == q ? tv : 0);
        const int ge = gb + gcnt;
        const int beg = gb;
        gb = ge;
        const bool own = beg >= ulo && (beg < uhi || un == 2);
        const int lo = max(beg, ulo), hi = min(ge, uhi);
        if (!own && lo >= hi) continue;
        uint32_t ra = sbase + MS_REC + (lo + ln) * 8;
        const int cnt = hi - beg;
        int rem = max(hi - lo, 0);
        const int lastcap = own ? 24 : 32;
        uint32_t flast = own ? 2u : 4u;
        if (own && un == 0 && beg < s1 && s1 < ge && s1 < s2) flast |= 16u;
        if (own && un < 2 && beg < s2 && s2 < ge) flast |= 32u;
        const unsigned char* svp = reinterpret_cast<const unsigned char*>(sv) +
                                   (size_t)(blockIdx.x * NPC + q * GRP + r4) * 512 + (ln & 7) * 16;
        auto fetch = [&](int left) -> uint2 {
            uint2 r = make_uint2(0, 0);
            if (FITS) {
                asm volatile("ld.shared.v2.u32 {%0,%1}, [%2];" : "=r"(r.x), "=r"(r.y) : "r"(ra));
                ra += 256;
            } else if (ln < left) {
                const int j = cnt - left + ln;
                const int* prq = reinterpret_cast<const int*>(smem + MS_B2) + q * 136;
                int lo = 0, hi = NCTA;
                while (hi - lo > 1) {
                    const int mid = (lo + hi) >> 1;
                    if (prq[mid] <= j) lo = mid; else hi = mid;
                }
                const int b0 = __ldcg(reinterpret_cast<const unsigned short*>(g_pfx + (lo * NCTA + blockIdx.x) * 2) + q + (q >= 7));
                r = __ldcg(g_rec + lo * CH + b0 + (j - prq[lo]));
            }
            return r;
        };
        uint2 rn = fetch(rem);
        bool last;
        do {
            const bool valid = ln < rem;
            last = rem <= lastcap;
            const bool svl = last && own;
            const uint2 r = valid ? rn : make_uint2(0, 0);
            rn = fetch(rem - 32);
            const uint32_t srcv = (r.y >> 16) & 0x7fffu;
            const unsigned char* gq[8];
#pragma unroll
            for (int k = 0; k < 8; k++)
                gq[k] = gsrc + (size_t)__shfl_sync(0xffffffffu, srcv, k * 4 + r4) * ROWB;
            const int lim = rem - r4;
            const int lim6 = svl ? nnodes - q * GRP + 24 - r4 : lim;
            if (svl) { gq[6] = svp; gq[7] = svp + 4 * 512; }
            const uint32_t rxy = hmul2(r.x & 0x9fff9fffu, 0x60806080u);
            const uint32_t rz2 = hmul2(r.y & 0x00009fffu, 0x60806080u);
            const uint32_t qxy = hmul2(rxy, rxy), qz = hmul2(rz2, rz2);
            const float sum = bf16r((__uint_as_float(qxy << 16) + __uint_as_float(qxy & 0xffff0000u)) + __uint_as_float(qz << 16));
            float sq;
            asm("sqrt.approx.ftz.f32 %0, %1;" : "=f"(sq) : "f"(bf16r(sum + 1e-8f)));
            const uint32_t dbits = pack_bf16(0.f, sq);
            float rinv;
            asm("rcp.approx.ftz.f32 %0, %1;" : "=f"(rinv) : "f"(__uint_as_float(dbits)));
            const int di = valid ? max(min((int)(dbits >> 16), DEND - 1) - DBASE, 0) : NTAB - 1;
            const uint4* gp = reinterpret_cast<const uint4*>(di >= HOT0 ? ghot : gcold) + 2 * di;
            const uint4 g0 = gp[0], g1 = gp[1];
            const uint32_t r01 = pack_bf16(__uint_as_float(rxy << 16) * rinv, __uint_as_float(rxy & 0xffff0000u) * rinv);
            const uint32_t r2 = pack_bf16(__uint_as_float(rz2 << 16) * rinv, valid ? 1.0f : 0.f);
            const uint32_t so = ((r.x >> 12) & 6u) | ((r.x >> 26) & 8u);
            const uint32_t fl = last ? (((uint32_t)q << 8) | flast) : 0u;

            const uint32_t bar = sb + ST_CTL;
            mbar_wait(bar + 8, ph);
            const uint32_t dpa = sb + d0, dpb = (dpa ^ 64u) + 512u;
#pragma unroll
            for (int k = 0; k < 8; k++) {
                asm volatile("{\n.reg .pred p;\nsetp.le.s32 p, %2, %3;\n"
                             "cp.async.cg.shared.global [%0], [%1], 16, p;\n"
                             "cp.async.cg.shared.global [%0+4096], [%1+128], 16, p;\n"
                             "cp.async.cg.shared.global [%0+8192], [%1+256], 16, p;\n"
                             "cp.async.cg.shared.global [%0+12288], [%1+384], 16, p;\n}\n"
                             ::"r"(((k & 1) ? dpb : dpa) + (k >> 1) * 1024), "l"(gq[k]), "r"(k < 6 ? lim : lim6), "r"(4 * k) : "memory");
            }
            asm volatile("cp.async.mbarrier.arrive.noinc.shared::cta.b64 [%0];" ::"r"(bar) : "memory");
            const uint32_t za = sb + ST_S + ln * 16;
            asm volatile("st.shared.v4.u32 [%0], {%1,%1,%1,%1};" ::"r"(za), "r"(0u) : "memory");
            asm volatile("st.shared.u16 [%0], %1;" ::"r"(za + so), "h"((unsigned short)(r2 >> 16)) : "memory");
            asm volatile("st.shared.u16 [%0], %1;" ::"r"(sb + roff), "h"((unsigned short)(r01 & 0xffffu)) : "memory");
            asm volatile("st.shared.u16 [%0+64], %1;" ::"r"(sb + roff), "h"((unsigned short)(r01 >> 16)) : "memory");
            asm volatile("st.shared.u16 [%0+128], %1;" ::"r"(sb + roff), "h"((unsigned short)(r2 & 0xffffu)) : "memory");
            asm volatile("st.shared.u32 [%0+16], %1;" ::"r"(bar), "r"(fl) : "memory");
            asm volatile("st.shared.v4.u32 [%0], {%1,%2,%3,%4};" ::"r"(sb + goff),
                         "r"(g0.x), "r"(g0.y), "r"(g0.z), "r"(g0.w) : "memory");
            asm volatile("st.shared.v4.u32 [%0], {%1,%2,%3,%4};" ::"r"((sb + goff) ^ 16u),
                         "r"(g1.x), "r"(g1.y), "r"(g1.z), "r"(g1.w) : "memory");
            asm volatile("fence.proxy.async.shared::cta;" ::: "memory");
            mbar_arrive(bar);
            sb += STAGE_BYTES;
            if (sb == ubase + STAGES * STAGE_BYTES) { sb = ubase; ph ^= 1; }
            rem -= 32;
        } while (!last);
    }
    const uint32_t bar = sb + ST_CTL;
    mbar_wait(bar + 8, ph);
    asm volatile("st.shared.u32 [%0+16], %1;" ::"r"(bar), "r"(8u) : "memory");
    mbar_arrive(bar);
    mbar_arrive(bar);
}

__global__ void __launch_bounds__(M_THREADS, 1)
fused_kernel(const __nv_bfloat16* __restrict__ sv, const __nv_bfloat16* __restrict__ pos,
             const int* __restrict__ src, const int* __restrict__ dst,
             const __nv_bfloat16* __restrict__ freqs, const __nv_bfloat16* __restrict__ w1,
             const __nv_bfloat16* __restrict__ w2, const __nv_bfloat16* __restrict__ wrbf,
             __nv_bfloat16* __restrict__ out, int N, int E) {
    extern __shared__ __align__(1024) unsigned char smem[];
    const int tid = threadIdx.x, lane = tid & 31;
    const int warp = (int)__reduce_or_sync(0xffffffffu, (uint32_t)tid >> 5);
    const uint32_t sbase = smem_u32(smem);
    const uint32_t ghbar = sbase + MS_BAR;
    int* misc = reinterpret_cast<int*>(smem + MS_MISC);
    const bool is_prod = warp >= UNITS * 4;
    const int cta = blockIdx.x;
    const int nnodes = min(NPC, N - cta * NPC);

    STAMP(0, 0);
    unsigned int epoch;
    asm volatile("ld.relaxed.gpu.global.u32 %0, [%1];" : "=r"(epoch) : "l"(&g_cnt));
    unsigned short freq_bits;
    asm volatile("ld.global.nc.u16 %0, [%1];" : "=h"(freq_bits) : "l"(freqs + (tid & 15)));
    const int nquad = max(min(EPC, E - cta * EPC), 0) >> 2;
    for (int i = tid; i < (N * 6 + 15) / 16; i += M_THREADS)
        cp_async16(sbase + PS_POS + i * 16, reinterpret_cast<const unsigned char*>(pos) + i * 16);
    asm volatile("cp.async.commit_group;" ::: "memory");
    int4 es[3], ed[3];
#pragma unroll
    for (int k = 0; k < 3; k++) {
        es[k] = ed[k] = make_int4(0, 0, 0, 0);
        if (tid + k * M_THREADS < nquad) {
            es[k] = __ldcs(reinterpret_cast<const int4*>(src + cta * EPC) + tid + k * M_THREADS);
            ed[k] = __ldcs(reinterpret_cast<const int4*>(dst + cta * EPC) + tid + k * M_THREADS);
        }
    }
    if (!is_prod) {
#pragma unroll
        for (int k = 0; k < 2; k++) {
            const int row = (warp & 3) * 8 + k * 4 + (lane >> 3);
            const int node = (warp >> 2) * 32 + row;
            asm volatile("{\n.reg .pred p;\nsetp.ge.s32 p, %2, %3;\n"
                         "cp.async.cg.shared.global [%0], [%1], 16, p;\n"
                         "cp.async.cg.shared.global [%0+4096], [%1+128], 16, p;\n"
                         "cp.async.cg.shared.global [%0+8192], [%1+256], 16, p;\n"
                         "cp.async.cg.shared.global [%0+12288], [%1+384], 16, p;\n}\n"
                         ::"r"(sbase + (warp >> 2) * STAGE_BYTES + row * 128 + (((lane ^ row) & 7) << 4)),
                           "l"(sv + (size_t)(cta * NPC + min(node, nnodes - 1)) * 256 + (lane & 7) * 8), "r"(node), "r"(nnodes) : "memory");
        }
        cp_async16(sbase + PS_WR + (tid / 24) * 400 + (tid % 24) * 16, wrbf + tid * 8);
    }
    {
        const int r = tid >> 3, c = tid & 7;
        cp_async16(sbase + PS_W1 + r * 144 + c * 16, w1 + tid * 8);
        cp_async16(sbase + PS_W2 + r * 272 + c * 16, w2 + r * 192 + c * 8);
        cp_async16(sbase + PS_WV + r * 144 + c * 16, w2 + r * 192 + 64 + c * 8);
        cp_async16(sbase + PS_W2 + r * 272 + 128 + c * 16, w2 + r * 192 + 128 + c * 8);
    }
    asm volatile("cp.async.commit_group;" ::: "memory");
    int* hist = reinterpret_cast<int*>(smem + PS_HIST);
    hist[tid] = 0; hist[tid + 512] = 0; hist[tid + 1024] = 0;
    if (warp == 15) {
        mbar_init(ghbar, 1);
        mbar_init(ghbar + 8, 128);
        mbar_init(ghbar + 16, 128);
        asm volatile("fence.mbarrier_init.release.cluster;" ::: "memory");
    }
    if (warp < 8 && cta * 16 < NTAB) {
        const float d = __uint_as_float((uint32_t)(DBASE + cta * 16 + (tid >> 4)) << 16);
        const float arg = bf16r(d * __uint_as_float((uint32_t)freq_bits << 16));
        float sn;
        if (fabsf(arg) < 1000.f) {
            const float k = rintf(arg * 0.15915494309189535f);
            sn = __sinf(fmaf(k, 1.7484556000744883e-7f, fmaf(k, -6.2831854820251465f, arg)));
        } else {
            sn = sinf(arg);
        }
        const float rbf = bf16r(__fdividef(bf16r(sn), d));
        const float ca = bf16r(bf16r(3.14159265358979f * d) * 0.2f);
        const float fc = 0.5f * bf16r(bf16r(__cosf(ca)) + 1.0f);
        g_G[cta * 256 + tid] = __float2bfloat16_rn(rbf * fc);
    }
    asm volatile("cp.async.wait_group 1;" ::: "memory");
    __syncthreads();
    STAMP(1, 0);
    {
        uint32_t rx[12], ry[12];
        int key[12];
#pragma unroll
        for (int e = 0; e < 12; e++) {
            const int k = e >> 2, b = e & 3;
            key[e] = -1;
            if (k < 2 || warp * 32 + 2 * M_THREADS < nquad) {
                const uint32_t sn = b == 0 ? es[k].x : b == 1 ? es[k].y : b == 2 ? es[k].z : es[k].w;
                const uint32_t dn = b == 0 ? ed[k].x : b == 1 ? ed[k].y : b == 2 ? ed[k].z : ed[k].w;
                const uint32_t as = sbase + PS_POS + sn * 6, ad = sbase + PS_POS + dn * 6;
                uint32_t sa, sb, da, db;
                asm volatile("ld.shared.u32 %0, [%2];\nld.shared.u32 %1, [%2+4];" : "=r"(sa), "=r"(sb) : "r"(as & ~3u));
                asm volatile("ld.shared.u32 %0, [%2];\nld.shared.u32 %1, [%2+4];" : "=r"(da), "=r"(db) : "r"(ad & ~3u));
                const uint32_t rxy = hsub2(__funnelshift_r(sa, sb, as << 3), __funnelshift_r(da, db, ad << 3));
                const uint32_t rz = hsub2(__funnelshift_r(sb, 0u, as << 3), __funnelshift_r(db, 0u, ad << 3));
                const uint32_t qxy = hmul2(rxy, rxy), qz = hmul2(rz, rz);
                const float sum = (__uint_as_float(qxy << 16) + __uint_as_float(qxy & 0xffff0000u)) + __uint_as_float(qz << 16);
                const uint32_t c = dn / NPC, dl = dn - c * NPC;
                rx[e] = hmul2(rxy, 0x1e801e80u) | ((dl * 0x08002000u) & 0x60006000u);
                ry[e] = __byte_perm(hmul2(rz, 0x1e801e80u), sn, 0x5410) | ((dl * 0x02000200u) & 0x80006000u);
                const int bin = c * NQ + (dl >> 3);
                if (sum < 23.9375f && tid + k * M_THREADS < nquad) key[e] = (bin << 13) | atomicAdd(&hist[bin], 1);
            }
        }
        asm volatile("cp.async.wait_all;" ::: "memory");
        asm volatile("fence.proxy.async.shared::cta;" ::: "memory");
        __syncthreads();
        STAMP(2, 0);
        if (is_prod) {
            const int pt = tid - UNITS * 128;
            int4* h4 = reinterpret_cast<int4*>(hist) + pt * 3;
            int4 a = h4[0], b = h4[1], c = h4[2];
            a.y += a.x; a.z += a.y; a.w += a.z; b.x += a.w; b.y += b.x; b.z += b.y; b.w += b.z;
            c.x += b.w; c.y += c.x; c.z += c.y; c.w += c.z;
            int incl = c.w;
#pragma unroll
            for (int o = 1; o < 32; o <<= 1) {
                const int v = __shfl_up_sync(0xffffffffu, incl, o);
                if (lane >= o) incl += v;
            }
            if (lane == 31) hist[1536 + warp - UNITS * 4] = incl;
            asm volatile("bar.sync 4, 128;" ::: "memory");
            const int ex = __reduce_add_sync(0xffffffffu, lane < warp - UNITS * 4 ? hist[1536 + lane] : 0) + incl - c.w;
            h4[0] = make_int4(ex, ex + a.x, ex + a.y, ex + a.z);
            h4[1] = make_int4(ex + a.w, ex + b.x, ex + b.y, ex + b.z);
            h4[2] = make_int4(ex + b.w, ex + c.x, ex + c.y, ex + c.z);
        } else {
            const int w = warp & 3;
            const uint32_t tb = sbase + (warp >> 2) * STAGE_BYTES;
            const int krow = (lane & 7) + 8 * (lane >> 4), mcol = 2 * w + ((lane >> 3) & 1);
            const uint32_t ta = tb + krow * 128 + ((uint32_t)(mcol ^ (lane & 7)) << 4);
            const uint32_t dh = (tb >> 4) | (1u << 16);
            uint32_t a[4][4];
            float d[16];
#pragma unroll
            for (int q = 0; q < 4; q++) ldsm4t(a[q], sbase + PS_W1 + (16 * q + krow) * 144 + mcol * 16);
            asm volatile("wgmma.fence.sync.aligned;" ::: "memory");
            wgmma_n32<0, DESC_H>(d, a[0], dh);
            wgmma_n32<1, DESC_H>(d, a[1], dh + 2);
            wgmma_n32<1, DESC_H>(d, a[2], dh + 4);
            wgmma_n32<1, DESC_H>(d, a[3], dh + 6);
            asm volatile("wgmma.commit_group.sync.aligned;" ::: "memory");
            asm volatile("wgmma.wait_group.sync.aligned 0;" ::: "memory");
            reg_fence16(d);
#pragma unroll
            for (int q = 0; q < 4; q++) ldsm4t(a[q], sbase + PS_WV + (16 * q + krow) * 144 + mcol * 16);
            uint32_t x[2][4];
#pragma unroll
            for (int i = 0; i < 8; i++) {
                const uint32_t z = pack_bf16(d[2 * i], d[2 * i + 1]);
                const float z0 = __uint_as_float(z << 16), z1 = __uint_as_float(z & 0xffff0000u);
                x[i >> 2][i & 3] = pack_bf16(__fdividef(z0, 1.0f + __expf(-z0)), __fdividef(z1, 1.0f + __expf(-z1)));
            }
            asm volatile("bar.sync %0, 128;" ::"r"(1 + (warp >> 2)) : "memory");
            stsm4t(ta, x[0]);
            stsm4t(ta + 2048, x[1]);
            asm volatile("fence.proxy.async.shared::cta;" ::: "memory");
            asm volatile("bar.sync %0, 128;" ::"r"(1 + (warp >> 2)) : "memory");
            STAMP(14, 0);
            asm volatile("wgmma.fence.sync.aligned;" ::: "memory");
            wgmma_n32<0, DESC_H>(d, a[0], dh);
            wgmma_n32<1, DESC_H>(d, a[1], dh + 2);
            wgmma_n32<1, DESC_H>(d, a[2], dh + 4);
            wgmma_n32<1, DESC_H>(d, a[3], dh + 6);
            asm volatile("wgmma.commit_group.sync.aligned;" ::: "memory");
            asm volatile("wgmma.wait_group.sync.aligned 0;" ::: "memory");
            reg_fence16(d);
#pragma unroll
            for (int i = 0; i < 8; i++) x[i >> 2][i & 3] = pack_bf16(d[2 * i], d[2 * i + 1]);
#pragma unroll
            for (int j = 1; j < 4; j++)
#pragma unroll
                for (int s = 0; s < 2; s++) {
                    uint32_t v[4];
                    ldsm4t(v, ta + j * 4096 + s * 2048);
#pragma unroll
                    for (int e = 0; e < 4; e++) v[e] = hmul2(v[e], x[s][e]);
                    stsm4t(ta + j * 4096 + s * 2048, v);
                }
            asm volatile("bar.sync %0, 128;" ::"r"(1 + (warp >> 2)) : "memory");
            STAMP(15, 0);
#pragma unroll
            for (int k = 0; k < 2; k++) {
                const int row = w * 8 + k * 4 + (lane >> 3);
                const int node = (warp >> 2) * 32 + row;
                if (node < nnodes) {
                    uint4* o = reinterpret_cast<uint4*>(g_tab + (size_t)(cta * NPC + node) * ROWB) + (lane & 7);
                    const unsigned char* ip = smem + (warp >> 2) * STAGE_BYTES + row * 128 + (((lane ^ row) & 7) << 4);
#pragma unroll
                    for (int c = 0; c < 4; c++) o[c * 8] = *reinterpret_cast<const uint4*>(ip + c * 4096);
                }
            }
        }
        __syncthreads();
        STAMP(3, 0);
        uint2* sorted = reinterpret_cast<uint2*>(smem + PS_POS);
#pragma unroll
        for (int e = 0; e < 12; e++)
            if (key[e] >= 0) sorted[hist[key[e] >> 13] + (key[e] & 8191)] = make_uint2(rx[e], ry[e]);
        __syncthreads();
        STAMP(4, 0);
        const int n16 = (hist[NBIN] + 1) >> 1;
#pragma unroll
        for (int k = 0; k < 5; k++)
            if (tid + k * M_THREADS < n16)
                reinterpret_cast<uint4*>(g_rec + cta * CH)[tid + k * M_THREADS] =
                    reinterpret_cast<const uint4*>(smem + PS_POS)[tid + k * M_THREADS];
        __syncthreads();
        STAMP(5, 0);
    }
    const int g = lane >> 2, t = lane & 3;
    unsigned short* pf = reinterpret_cast<unsigned short*>(smem + PS_PF);
    int* b2 = reinterpret_cast<int*>(smem + MS_B2);
    {
        const uint32_t tag = ((epoch / NCTA + 1) & 0xffffu) << 16;
        if (warp < 9) {
            const int c = min(tid >> 1, NCTA - 1);
            const int* h = hist + c * NQ + (tid & 1) * 7;
            uint4 v = make_uint4(h[0] | (h[1] << 16), h[2] | (h[3] << 16), h[4] | (h[5] << 16), h[6] | tag);
            __threadfence();
            asm volatile("st.relaxed.gpu.global.v4.u32 [%0], {%1,%2,%3,%4};" ::"l"(g_pfx + (cta * NCTA + c) * 2 + (tid & 1)),
                         "r"(v.x), "r"(v.y), "r"(v.z), "r"(v.w) : "memory");
        } else if (warp == 15) {
            if (lane < UNITS * STAGES) {
                mbar_init(sbase + lane * STAGE_BYTES + ST_CTL, 64);
                mbar_init(sbase + lane * STAGE_BYTES + ST_CTL + 8, 4);
                asm volatile("fence.mbarrier_init.release.cluster;" ::: "memory");
            }
            if (lane == 31) atomicInc(&g_cnt, NCTA * 65536u - 1);
        }
        STAMP(6, 0);
        const int p = min(warp + 16 * (lane >> 1), NCTA - 1);
        uint4 v;
        int spin = 0;
        do {
            asm volatile("ld.acquire.gpu.global.v4.u32 {%0,%1,%2,%3}, [%4];" : "=r"(v.x), "=r"(v.y), "=r"(v.z), "=r"(v.w)
                         : "l"(g_pfx + (p * NCTA + cta) * 2 + (lane & 1)) : "memory");
        } while (__any_sync(0xffffffffu, (v.w ^ tag) & 0xffff0000u) && ++spin < (1 << 22));
        STAMP(7, 0);
        reinterpret_cast<uint4*>(pf)[p * 2 + (lane & 1)] = v;
#pragma unroll
        for (int k = 0; k < 9; k++) {
            const int pp = warp + 16 * k;
            const int i = (__shfl_sync(0xffffffffu, v.x, 2 * k) & 0xfffe) + 2 * lane;
            const int e = __shfl_sync(0xffffffffu, v.y, 2 * k + 1) >> 16;
            if (i < e && pp < NCTA)
                cp_async16(sbase + (3 + (pp >> 5)) * STAGE_BYTES + (pp & 31) * 512 + lane * 16, g_rec + pp * CH + i);
        }
        __syncthreads();
        STAMP(9, 0);
        if (warp < NQ) {
            const int q = warp;
            int cq[5], sum = 0;
#pragma unroll
            for (int k = 0; k < 5; k++) {
                const int pp = min(lane * 5 + k, NCTA - 1);
                cq[k] = lane * 5 + k < NCTA ? pf[pp * 16 + q + 1 + (q >= 6)] - pf[pp * 16 + q + (q >= 7)] : 0;
                sum += cq[k];
            }
            int in2 = sum;
#pragma unroll
            for (int o = 1; o < 32; o <<= 1) {
                const int x = __shfl_up_sync(0xffffffffu, in2, o);
                if (lane >= o) in2 += x;
            }
            int pre = in2 - sum;
            if (lane == 31) misc[q] = in2;
#pragma unroll
            for (int k = 0; k < 5; k++) {
                if (lane * 5 + k < NCTA) b2[q * 136 + lane * 5 + k] = pre;
                pre += cq[k];
            }
        } else {
            for (int i = tid - NQ * 32; i < (NTAB - HOT0) * 2; i += M_THREADS - NQ * 32)
                cp_async16(sbase + MS_GH + i * 16, g_G + HOT0 * NRBF + i * 8);
        }
        asm volatile("cp.async.wait_all;" ::: "memory");
    }
    __syncthreads();
    STAMP(11, 0);
    {
        int gbase = lane < NQ ? misc[lane] : 0;
#pragma unroll
        for (int o = 1; o < 16; o <<= 1) {
            const int v = __shfl_up_sync(0xffffffffu, gbase, o);
            if (lane >= o) gbase += v;
        }
        const bool fits = __reduce_max_sync(0xffffffffu, gbase) <= RCAP;
        gbase = __shfl_up_sync(0xffffffffu, gbase, 1);
        if (lane == 0) gbase = 0;
        if (fits) {
            uint2* srec = reinterpret_cast<uint2*>(smem + MS_REC);
            bool more = false;
#pragma unroll
            for (int k = 0; k < 9; k++) {
                const int p = min(warp + 16 * k, NCTA - 1);
                const int beg = pf[p * 16], end = warp + 16 * k < NCTA ? pf[p * 16 + NQ + 1] : 0;
                const uint2 v = reinterpret_cast<const uint2*>(smem + (3 + (p >> 5)) * STAGE_BYTES + (p & 31) * 512)[(beg & 1) + lane];
                const int q = min((int)(((v.x >> 30) & 1u) | ((v.y >> 12) & 6u) | ((v.y >> 28) & 8u)), NQ - 1);
                const int o = __shfl_sync(0xffffffffu, gbase, q) + b2[q * 136 + p] - pf[p * 16 + q + (q >= 7)];
                if (beg + lane < end) srec[o + beg + lane] = v;
                more |= beg + 32 < end;
            }
            if (more) {
#pragma unroll 1
                for (int p = warp; p < NCTA; p += 16) {
                    const int beg = pf[p * 16], end = pf[p * 16 + NQ + 1];
                    const uint2* raw = reinterpret_cast<const uint2*>(smem + (3 + (p >> 5)) * STAGE_BYTES + (p & 31) * 512);
#pragma unroll 1
                    for (int i0 = beg + 32; i0 < end; i0 += 32) {
                        const int i = i0 + lane, o = i - (beg & ~1);
                        uint2 v = make_uint2(0, 0);
                        if (i < end) v = o < 64 ? raw[o] : __ldcg(g_rec + p * CH + i);
                        const int q = (int)(((v.x >> 30) & 1u) | ((v.y >> 12) & 6u) | ((v.y >> 28) & 8u));
                        const int gb = __shfl_sync(0xffffffffu, gbase, q);
                        if (i < end) srec[gb + b2[q * 136 + p] - pf[p * 16 + q + (q >= 7)] + i] = v;
                    }
                }
            }
        }
        __syncthreads();
    }
    STAMP(12, 0);

    if (is_prod) {
        asm volatile("setmaxnreg.dec.sync.aligned.u32 80;");
        const int unit = warp - UNITS * 4;
        if (unit < UNITS) {
            asm volatile("bar.sync 6, 480;" ::: "memory");
            STAMP(21, 384);
            if (__reduce_add_sync(0xffffffffu, lane < NQ ? misc[lane] : 0) <= RCAP) producer_loop<true>(smem, sv, N, unit);
            else producer_loop<false>(smem, sv, N, unit);
            STAMP(22 + unit, 384 + 32 * unit);
        }
    } else {
        asm volatile("setmaxnreg.inc.sync.aligned.u32 144;");
        const int unit = warp >> 2, w = warp & 3;
        const uint32_t ubase = sbase + unit * STAGES * STAGE_BYTES;
        uint32_t wa[3][4], pa[2][4][4];
        {
            const int krow = (lane & 7) + 8 * (lane >> 4), mcol = 2 * w + ((lane >> 3) & 1);
#pragma unroll
            for (int q = 0; q < 4; q++) {
                ldsm4t(pa[0][q], sbase + PS_W2 + (16 * q + krow) * 272 + mcol * 16);
                ldsm4t(pa[1][q], sbase + PS_W2 + (16 * q + krow) * 272 + 128 + mcol * 16);
            }
#pragma unroll
            for (int p = 0; p < 3; p++) ldsm4t(wa[p], sbase + PS_WR + krow * 400 + p * 128 + mcol * 16);
            asm volatile("bar.arrive 6, 480;" ::: "memory");
        }
        float acc[4][4];
#pragma unroll
        for (int c = 0; c < 4; c++)
#pragma unroll
            for (int e = 0; e < 4; e++) acc[c][e] = 0.f;
        const int erow = (lane & 7) + 8 * (lane >> 4);
        const int ehalf = (lane >> 3) & 1;
        const uint32_t ua = pin(4096 + erow * 128 + ((uint32_t)((2 * w + ehalf) ^ (lane & 7)) << 4));
        const uint32_t sa = pin(ST_S + lane * 16);
        const uint32_t ra = pin(ST_R + t * 16);
        const uint32_t ub = __reduce_or_sync(0xffffffffu, ubase);
        uint32_t sb = ub;
        uint32_t ph = 0;
        const bool elected = sa == ST_S;
        while (true) {
            mbar_wait(sb + ST_CTL, ph);
            {
                const uint32_t dh = (sb >> 4) | (1u << 16);
                const uint32_t dg = dh + (ST_G >> 4);
                uint32_t m[2][4], wv[2][4], u[3][4], sf[4], rr[3][2];
                float p0[16], f0[16], fv[16];
                asm volatile("wgmma.fence.sync.aligned;" ::: "memory");
                wgmma_n32<0, DESC_G>(f0, wa[2], dg);
                wgmma_n32<0, DESC_H>(p0, pa[1][0], dh);
                wgmma_n32<1, DESC_H>(p0, pa[1][1], dh + 2);
                wgmma_n32<1, DESC_H>(p0, pa[1][2], dh + 4);
                wgmma_n32<1, DESC_H>(p0, pa[1][3], dh + 6);
                wgmma_n32<0, DESC_G>(fv, wa[1], dg);
                asm volatile("wgmma.commit_group.sync.aligned;" ::: "memory");
#pragma unroll
                for (int j = 0; j < 3; j++) {
                    ldsm4t(u[j], sb + ua + j * 4096);
                    asm volatile("ld.shared.v2.u32 {%0,%1}, [%2];" : "=r"(rr[j][0]), "=r"(rr[j][1]) : "r"(sb + ra + j * 64));
                }
                ldsm4t(sf, sb + sa);
                asm volatile("wgmma.wait_group.sync.aligned 0;" ::: "memory");
                reg_fence16(fv); reg_fence16(f0); reg_fence16(p0);
#pragma unroll
                for (int i = 0; i < 8; i++) {
                    m[i >> 2][i & 3] = pack_bf16(f0[2 * i] * p0[2 * i], f0[2 * i + 1] * p0[2 * i + 1]);
                    wv[i >> 2][i & 3] = pack_bf16(fv[2 * i], fv[2 * i + 1]);
                }
                asm volatile("wgmma.fence.sync.aligned;" ::: "memory");
                wgmma_n32<0, DESC_G>(f0, wa[0], dg);
                wgmma_n32<0, DESC_H>(p0, pa[0][0], dh);
                wgmma_n32<1, DESC_H>(p0, pa[0][1], dh + 2);
                wgmma_n32<1, DESC_H>(p0, pa[0][2], dh + 4);
                wgmma_n32<1, DESC_H>(p0, pa[0][3], dh + 6);
                asm volatile("wgmma.commit_group.sync.aligned;" ::: "memory");
                uint32_t v1[3][4];
#pragma unroll
                for (int j = 0; j < 3; j++)
#pragma unroll
                    for (int e = 0; e < 4; e++) u[j][e] = hfma2(m[0][e], rr[j][e >> 1], hmul2(u[j][e], wv[0][e]));
#pragma unroll
                for (int j = 0; j < 3; j++) {
                    ldsm4t(v1[j], sb + ua + j * 4096 + 2048);
                    asm volatile("ld.shared.v2.u32 {%0,%1}, [%2];" : "=r"(rr[j][0]), "=r"(rr[j][1]) : "r"(sb + ra + j * 64 + 8));
                }
#pragma unroll
                for (int j = 0; j < 3; j++)
#pragma unroll
                    for (int e = 0; e < 4; e++) v1[j][e] = hfma2(m[1][e], rr[j][e >> 1], hmul2(v1[j][e], wv[1][e]));
#pragma unroll
                for (int j = 0; j < 3; j++) mma16816(acc[j + 1], u[j], sf[0], sf[1]);
#pragma unroll
                for (int j = 0; j < 3; j++) mma16816(acc[j + 1], v1[j], sf[2], sf[3]);
                asm volatile("wgmma.wait_group.sync.aligned 0;" ::: "memory");
                reg_fence16(f0); reg_fence16(p0);
#pragma unroll
                for (int i = 0; i < 8; i++)
                    m[i >> 2][i & 3] = pack_bf16(f0[2 * i] * p0[2 * i], f0[2 * i + 1] * p0[2 * i + 1]);
                mma16816(acc[0], m[0], sf[0], sf[1]);
                mma16816(acc[0], m[1], sf[2], sf[3]);
            }
            uint32_t flags;
            asm volatile("ld.shared.u32 %0, [%1+16];" : "=r"(flags) : "r"(sb + ST_CTL));
            if (flags) {
                if (flags & 8u) break;
                float* part = reinterpret_cast<float*>(smem + MS_PART) + (tid & 127);
                if (flags & 4u) {
#pragma unroll
                    for (int i = 0; i < 16; i++) part[(unit - 1) * 2048 + i * 128] = acc[i >> 2][i & 3];
                    mbar_arrive(sbase + MS_BAR + unit * 8);
                } else {
#pragma unroll 1
                    for (int k = 0; k < 2; k++) {
                        if (flags & (16u << k)) {
                            mbar_wait(sbase + MS_BAR + 8 + k * 8, 0);
#pragma unroll
                            for (int i = 0; i < 16; i++) acc[i >> 2][i & 3] += part[k * 2048 + i * 128];
                        }
                    }
                    const uint32_t ea = sb + (lane >> 4) * 4096 + (24 + (lane & 7)) * 128 +
                                        ((uint32_t)((2 * w + ((lane >> 3) & 1)) ^ (lane & 7)) << 4);
#pragma unroll
                    for (int k = 0; k < 2; k++) {
                        uint32_t v[4];
                        ldsm4t(v, ea + k * 8192);
#pragma unroll
                        for (int e = 0; e < 4; e++)
                            v[e] = pack_bf16(__uint_as_float(v[e] << 16) + acc[2 * k + (e >> 1)][2 * (e & 1)],
                                             __uint_as_float(v[e] & 0xffff0000u) + acc[2 * k + (e >> 1)][2 * (e & 1) + 1]);
                        stsm4t(ea + k * 8192, v);
                    }
                    __syncwarp();
                    const int ln0 = (int)(flags >> 8) * GRP + (lane >> 2);
                    const int c0 = (lane >> 1) & 1, ch = 2 * w + (lane & 1);
                    uint4* op = reinterpret_cast<uint4*>(out + (size_t)(blockIdx.x * NPC + ln0) * 256) + c0 * 8 + ch;
                    const uint32_t ia = sb + c0 * 4096 + (24 + (lane >> 2)) * 128 + ((uint32_t)(ch ^ (lane >> 2)) << 4);
#pragma unroll
                    for (int k = 0; k < 2; k++) {
                        asm volatile("{\n.reg .pred p;\n.reg .b32 a, b, c, d;\nsetp.lt.s32 p, %2, %3;\n"
                                     "ld.shared.v4.u32 {a, b, c, d}, [%0];\n"
                                     "@p st.global.v4.u32 [%1], {a, b, c, d};\n}\n"
                                     ::"r"(ia + k * 8192), "l"(op + k * 16), "r"(ln0), "r"(min(NPC, N - (int)blockIdx.x * NPC)) : "memory");
                    }
                }
#pragma unroll
                for (int i = 0; i < 16; i++) acc[i >> 2][i & 3] = 0.f;
            }
            __syncwarp();
            if (elected) mbar_arrive(sb + ST_CTL + 8);
            sb += STAGE_BYTES;
            if (sb == ub + STAGES * STAGE_BYTES) { sb = ub; ph ^= 1; }
        }
        STAMP(26 + unit, 128 * unit);
    }
}

}

extern "C" void kernel_launch(void* const* d_in, const int* in_sizes, int n_in, void* d_out, int out_size) {
    const __nv_bfloat16* sv = (const __nv_bfloat16*)d_in[0];
    const __nv_bfloat16* pos = (const __nv_bfloat16*)d_in[1];
    const int* src = (const int*)d_in[2];
    const int* dst = (const int*)d_in[3];
    const __nv_bfloat16* freqs = (const __nv_bfloat16*)d_in[4];
    const __nv_bfloat16* w1 = (const __nv_bfloat16*)d_in[5];
    const __nv_bfloat16* w2 = (const __nv_bfloat16*)d_in[6];
    const __nv_bfloat16* wrbf = (const __nv_bfloat16*)d_in[7];
    __nv_bfloat16* out = (__nv_bfloat16*)d_out;
    const int N = in_sizes[1] / 3;
    const int E = in_sizes[2];

    static bool init = false;
    if (!init) {
        cudaFuncSetAttribute(fused_kernel, cudaFuncAttributeMaxDynamicSharedMemorySize, M_SMEM);
        init = true;
    }
    fused_kernel<<<NCTA, M_THREADS, M_SMEM, cudaStreamPerThread>>>(sv, pos, src, dst, freqs, w1, w2, wrbf, out, N, E);
}
```

```cpp
#include <cuda_runtime.h>
#include <cuda_bf16.h>
#include <stdint.h>

namespace {

constexpr int D = 64;
constexpr int NRBF = 16;
constexpr int MAXN = 10000;
constexpr int MAXE = 640000;
constexpr int NCTA = 132;
constexpr int GRP = 8;
constexpr int NPC = (MAXN + NCTA - 1) / NCTA;
constexpr int NQ = (NPC + GRP - 1) / GRP;
constexpr int NBIN = NCTA * NQ;
constexpr int CH = 4864;
constexpr int DBASE = 0x38C0;
constexpr int DEND = 0x40A0;
constexpr int NTAB = DEND - DBASE;
constexpr int ROWB = 512;

__device__ __align__(128) unsigned char g_tab[(size_t)(MAXN + 16) * ROWB];
__device__ __align__(128) __nv_bfloat16 g_G[NTAB * NRBF];
__device__ __align__(128) uint2 g_rec[NCTA * CH];
__device__ __align__(128) uint4 g_pfx[NCTA * NCTA * 2];
__device__ unsigned int g_cnt;

#define STAMP(k, tt) do {} while (0)
#define GSTAMP(k, tt) do {} while (0)

__device__ __forceinline__ uint32_t smem_u32(const void* p) { return (uint32_t)__cvta_generic_to_shared(p); }
__device__ __forceinline__ uint32_t pack_bf16(float lo, float hi) {
    uint32_t r;
    asm("cvt.rn.bf16x2.f32 %0, %1, %2;" : "=r"(r) : "f"(hi), "f"(lo));
    return r;
}
__device__ __forceinline__ float bf16r(float x) { return __uint_as_float(pack_bf16(0.f, x) & 0xffff0000u); }
__device__ __forceinline__ uint32_t hmul2(uint32_t a, uint32_t b) {
    uint32_t r;
    asm("mul.rn.bf16x2 %0, %1, %2;" : "=r"(r) : "r"(a), "r"(b));
    return r;
}
__device__ __forceinline__ uint32_t hsub2(uint32_t a, uint32_t b) {
    uint32_t r;
    asm("sub.rn.bf16x2 %0, %1, %2;" : "=r"(r) : "r"(a), "r"(b));
    return r;
}
__device__ __forceinline__ uint32_t hfma2(uint32_t a, uint32_t b, uint32_t c) {
    uint32_t r;
    asm("fma.rn.bf16x2 %0, %1, %2, %3;" : "=r"(r) : "r"(a), "r"(b), "r"(c));
    return r;
}
__device__ __forceinline__ void mma16816(float (&c)[4], const uint32_t (&a)[4], uint32_t b0, uint32_t b1) {
    asm volatile("mma.sync.aligned.m16n8k16.row.col.f32.bf16.bf16.f32 {%0,%1,%2,%3}, {%4,%5,%6,%7}, {%8,%9}, {%0,%1,%2,%3};"
                 : "+f"(c[0]), "+f"(c[1]), "+f"(c[2]), "+f"(c[3])
                 : "r"(a[0]), "r"(a[1]), "r"(a[2]), "r"(a[3]), "r"(b0), "r"(b1));
}
__device__ __forceinline__ void mma16816_z(float (&c)[4], const uint32_t (&a)[4], uint32_t b0, uint32_t b1) {
    asm volatile("mma.sync.aligned.m16n8k16.row.col.f32.bf16.bf16.f32 {%0,%1,%2,%3}, {%4,%5,%6,%7}, {%8,%9}, {%10,%10,%10,%10};"
                 : "=f"(c[0]), "=f"(c[1]), "=f"(c[2]), "=f"(c[3])
                 : "r"(a[0]), "r"(a[1]), "r"(a[2]), "r"(a[3]), "r"(b0), "r"(b1), "f"(0.f));
}
__device__ __forceinline__ void ldsm4(uint32_t (&r)[4], uint32_t addr) {
    asm volatile("ldmatrix.sync.aligned.m8n8.x4.shared.b16 {%0,%1,%2,%3}, [%4];"
                 : "=r"(r[0]), "=r"(r[1]), "=r"(r[2]), "=r"(r[3]) : "r"(addr));
}
__device__ __forceinline__ void ldsm4t(uint32_t (&r)[4], uint32_t addr) {
    asm volatile("ldmatrix.sync.aligned.m8n8.x4.trans.shared.b16 {%0,%1,%2,%3}, [%4];"
                 : "=r"(r[0]), "=r"(r[1]), "=r"(r[2]), "=r"(r[3]) : "r"(addr));
}
__device__ __forceinline__ void stsm4t(uint32_t addr, const uint32_t (&r)[4]) {
    asm volatile("stmatrix.sync.aligned.m8n8.x4.trans.shared.b16 [%0], {%1,%2,%3,%4};"
                 ::"r"(addr), "r"(r[0]), "r"(r[1]), "r"(r[2]), "r"(r[3]) : "memory");
}
__device__ __forceinline__ void cp_async16(uint32_t dst, const void* src) {
    asm volatile("cp.async.cg.shared.global [%0], [%1], 16;" ::"r"(dst), "l"(src) : "memory");
}
__device__ __forceinline__ void mbar_init(uint32_t bar, int cnt) {
    asm volatile("mbarrier.init.shared::cta.b64 [%0], %1;" ::"r"(bar), "r"(cnt) : "memory");
}
__device__ __forceinline__ void mbar_arrive(uint32_t bar) {
    asm volatile("mbarrier.arrive.shared::cta.b64 _, [%0];" ::"r"(bar) : "memory");
}
__device__ __forceinline__ void mbar_expect_tx(uint32_t bar, uint32_t bytes) {
    asm volatile("mbarrier.arrive.expect_tx.shared::cta.b64 _, [%0], %1;" ::"r"(bar), "r"(bytes) : "memory");
}
__device__ __forceinline__ void mbar_wait(uint32_t bar, uint32_t parity) {
    asm volatile(
        "{\n.reg .pred p;\n.reg .u32 n;\nmov.u32 n, 0;\n"
        "WAIT_%=:\n"
        "mbarrier.try_wait.parity.shared::cta.b64 p, [%0], %1, %2;\n"
        "@p bra DONE_%=;\n"
        "add.u32 n, n, 1;\n"
        "setp.lt.u32 p, n, 100000;\n"
        "@p bra WAIT_%=;\n"
        "exit;\n"
        "DONE_%=:\n}\n" ::"r"(bar), "r"(parity), "r"(10000u) : "memory");
}
__device__ __forceinline__ void bulk_g2s(uint32_t dst, const void* src, uint32_t bytes, uint32_t bar) {
    asm volatile("cp.async.bulk.shared::cluster.global.mbarrier::complete_tx::bytes [%0], [%1], %2, [%3];"
                 ::"r"(dst), "l"(src), "r"(bytes), "r"(bar) : "memory");
}
__device__ __forceinline__ void bulk_s2g(void* dst, uint32_t src, uint32_t bytes) {
    asm volatile("cp.async.bulk.global.shared::cta.bulk_group [%0], [%1], %2;" ::"l"(dst), "r"(src), "r"(bytes) : "memory");
}

constexpr int UNITS = 3;
constexpr int STAGES = 3;
constexpr int M_THREADS = UNITS * 128 + 128;
constexpr int ST_G = 4 * 4096;
constexpr int ST_S = ST_G + 1024;
constexpr int ST_R = ST_S + 512;
constexpr int ST_CTL = ST_R + 192;
constexpr int STAGE_BYTES = ST_S + 1024;
constexpr int RCAP = 3776;
constexpr int HOT0 = 0x3F00 - DBASE;
constexpr int MS_REC = UNITS * STAGES * STAGE_BYTES;
constexpr int MS_PART = MS_REC + RCAP * 8;
constexpr int MS_GH = MS_PART + 2 * 8192;
constexpr int MS_B2 = MS_GH + (NTAB - HOT0) * 32;
constexpr int MS_MISC = MS_B2 + 1536 * 4;
constexpr int MS_BAR = MS_MISC + 32 * 4;
constexpr int MS_DBG = MS_BAR + 64;
constexpr int M_SMEM = MS_DBG + 256;
constexpr int EPC = 4852;
constexpr int PS_POS = UNITS * STAGE_BYTES;
constexpr int PS_W1 = PS_POS + 60032;
constexpr int PS_WR = 7 * STAGE_BYTES + 4096;
constexpr int PS_HIST = PS_WR + 16 * 400;
constexpr int PS_W2 = 8 * STAGE_BYTES;
constexpr int PS_SRC = MS_REC;
constexpr int PS_DST = PS_SRC + CH * 4;
constexpr int PS_KEY = PS_DST + CH * 4;
constexpr int PS_PF = MS_PART;
static_assert(PS_W1 % 128 == 0 && PS_W1 + 16384 <= PS_WR && PS_HIST + (1536 + 32) * 4 <= 7 * STAGE_BYTES + ST_CTL &&
              64 * 272 <= ST_CTL && PS_KEY + CH * 4 <= MS_B2 && EPC * NCTA >= MAXE && EPC <= CH && CH * 8 <= 60032,
              "phase-1 layout");
static_assert(M_SMEM <= 232448, "smem");
static_assert(MS_BAR % 8 == 0 && MS_GH % 16 == 0 && STAGE_BYTES % 1024 == 0, "align");

template <int ACC, uint32_t HI>
__device__ __forceinline__ void wgmma_n32(float (&d)[16], const uint32_t (&a)[4], uint32_t lo) {
    if (ACC) {
        asm volatile("{\n.reg .b64 dd;\nmov.b64 dd, {%20, %21};\n"
                     "wgmma.mma_async.sync.aligned.m64n32k16.f32.bf16.bf16 {%0,%1,%2,%3,%4,%5,%6,%7,%8,%9,%10,%11,%12,%13,%14,%15}, {%16,%17,%18,%19}, dd, 1, 1, 1, 0;\n}\n"
                     : "+f"(d[0]), "+f"(d[1]), "+f"(d[2]), "+f"(d[3]), "+f"(d[4]), "+f"(d[5]), "+f"(d[6]), "+f"(d[7]),
                       "+f"(d[8]), "+f"(d[9]), "+f"(d[10]), "+f"(d[11]), "+f"(d[12]), "+f"(d[13]), "+f"(d[14]), "+f"(d[15])
                     : "r"(a[0]), "r"(a[1]), "r"(a[2]), "r"(a[3]), "r"(lo), "n"(HI));
    } else {
        asm volatile("{\n.reg .b64 dd;\nmov.b64 dd, {%20, %21};\n"
                     "wgmma.mma_async.sync.aligned.m64n32k16.f32.bf16.bf16 {%0,%1,%2,%3,%4,%5,%6,%7,%8,%9,%10,%11,%12,%13,%14,%15}, {%16,%17,%18,%19}, dd, 0, 1, 1, 0;\n}\n"
                     : "=f"(d[0]), "=f"(d[1]), "=f"(d[2]), "=f"(d[3]), "=f"(d[4]), "=f"(d[5]), "=f"(d[6]), "=f"(d[7]),
                       "=f"(d[8]), "=f"(d[9]), "=f"(d[10]), "=f"(d[11]), "=f"(d[12]), "=f"(d[13]), "=f"(d[14]), "=f"(d[15])
                     : "r"(a[0]), "r"(a[1]), "r"(a[2]), "r"(a[3]), "r"(lo), "n"(HI));
    }
}
constexpr uint32_t DESC_H = 64u | (1u << 30);
constexpr uint32_t DESC_G = 16u | (3u << 30);
__device__ __forceinline__ void reg_fence16(float (&d)[16]) {
    asm volatile("" : "+f"(d[0]), "+f"(d[1]), "+f"(d[2]), "+f"(d[3]), "+f"(d[4]), "+f"(d[5]), "+f"(d[6]), "+f"(d[7]),
                      "+f"(d[8]), "+f"(d[9]), "+f"(d[10]), "+f"(d[11]), "+f"(d[12]), "+f"(d[13]), "+f"(d[14]), "+f"(d[15]) :: "memory");
}
__device__ __forceinline__ uint32_t pin(uint32_t x) { return __shfl_sync(0xffffffffu, x, threadIdx.x & 31); }

__device__ __forceinline__ void scan1536(int* h, int pt) {
    int4* h4 = reinterpret_cast<int4*>(h) + pt * 3;
    int4 a = h4[0], b = h4[1], c = h4[2];
    a.y += a.x; a.z += a.y; a.w += a.z; b.x += a.w; b.y += b.x; b.z += b.y; b.w += b.z;
    c.x += b.w; c.y += c.x; c.z += c.y; c.w += c.z;
    int incl = c.w;
#pragma unroll
    for (int o = 1; o < 32; o <<= 1) {
        const int v = __shfl_up_sync(0xffffffffu, incl, o);
        if ((pt & 31) >= o) incl += v;
    }
    if ((pt & 31) == 31) h[1536 + (pt >> 5)] = incl;
    asm volatile("bar.sync 4, 128;" ::: "memory");
    const int ex = __reduce_add_sync(0xffffffffu, (pt & 31) < (pt >> 5) ? h[1536 + (pt & 31)] : 0) + incl - c.w;
    h4[0] = make_int4(ex, ex + a.x, ex + a.y, ex + a.z);
    h4[1] = make_int4(ex + a.w, ex + b.x, ex + b.y, ex + b.z);
    h4[2] = make_int4(ex + b.w, ex + c.x, ex + c.y, ex + c.z);
}

template <bool FITS>
__device__ __forceinline__ void producer_loop(unsigned char* smem, const __nv_bfloat16* __restrict__ sv, int N, int unit) {
    const uint32_t sbase = smem_u32(smem);
    const uint32_t ubase = __reduce_or_sync(0xffffffffu, sbase + unit * STAGES * STAGE_BYTES);
    const int* b2 = reinterpret_cast<const int*>(smem + MS_B2);
    const int ln = pin(threadIdx.x & 31);
    const int r4 = ln >> 3;
    const unsigned char* gsrc = g_tab + (ln & 7) * 16;
    asm volatile("" : "+l"(gsrc));
    const uint32_t d0 = r4 * 128 + (((ln & 7) ^ r4) << 4);
    const uint32_t goff = ST_G + ln * 32 + (((ln >> 2) & 1) << 4);
    const uint32_t roff = ST_R + ((ln >> 1) & 3) * 16 + (ln >> 3) * 4 + (ln & 1) * 2;
    const unsigned char* ghot = smem + (MS_GH - HOT0 * 32);
    const unsigned char* gcold = reinterpret_cast<const unsigned char*>(g_G);
    asm volatile("" : "+l"(ghot), "+l"(gcold));
    uint32_t sb = ubase, ph = 1;
    const int total = (int)__reduce_or_sync(0xffffffffu, (uint32_t)b2[NBIN]);
    const int s1 = total / 3, s2 = (2 * total) / 3;
    const int un = (int)__reduce_or_sync(0xffffffffu, (uint32_t)unit);
    const int ulo = un == 0 ? 0 : (un == 1 ? s1 : s2);
    const int uhi = un == 0 ? s1 : (un == 1 ? s2 : total);
    const int nnodes = min(NPC, N - (int)blockIdx.x * NPC);
    int gb = 0;
    for (int q = 0; q < NQ; q++) {
        const int ge = (int)__reduce_or_sync(0xffffffffu, (uint32_t)b2[(q + 1) * NCTA]);
        const int beg = gb;
        gb = ge;
        const bool own = beg >= ulo && (beg < uhi || un == 2);
        const int lo = max(beg, ulo), hi = min(ge, uhi);
        if (!own && lo >= hi) continue;
        uint32_t ra = sbase + MS_REC + (lo + ln) * 8;
        int rem = max(hi - lo, 0);
        const int lastcap = own ? 24 : 32;
        uint32_t flast = own ? 2u : 4u;
        if (own && un == 0 && beg < s1 && s1 < ge && s1 < s2) flast |= 16u;
        if (own && un < 2 && beg < s2 && s2 < ge) flast |= 32u;
        const unsigned char* svp = reinterpret_cast<const unsigned char*>(sv) +
                                   (size_t)(blockIdx.x * NPC + q * GRP + r4) * 512 + (ln & 7) * 16;
        auto fetch = [&](int left) -> uint2 {
            uint2 r = make_uint2(0, 0);
            if (FITS) {
                asm volatile("ld.shared.v2.u32 {%0,%1}, [%2];" : "=r"(r.x), "=r"(r.y) : "r"(ra));
                ra += 256;
            } else if (ln < left) {
                const int j = hi - left + ln;
                const int* prq = b2 + q * NCTA;
                int lo = 0, up = NCTA;
                while (up - lo > 1) {
                    const int mid = (lo + up) >> 1;
                    if (prq[mid] <= j) lo = mid; else up = mid;
                }
                const int b0 = __ldcg(reinterpret_cast<const unsigned short*>(g_pfx + (lo * NCTA + blockIdx.x) * 2) + q + (q >= 7));
                r = __ldcg(g_rec + lo * CH + b0 + (j - prq[lo]));
            }
            return r;
        };
        uint2 rn = fetch(rem);
        bool last;
        do {
            const bool valid = ln < rem;
            last = rem <= lastcap;
            const bool svl = last && own;
            const uint2 r = valid ? rn : make_uint2(0, 0);
            rn = fetch(rem - 32);
            const uint32_t srcv = (r.y >> 16) & 0x7fffu;
            const unsigned char* gq[8];
#pragma unroll
            for (int k = 0; k < 8; k++)
                gq[k] = gsrc + (size_t)__shfl_sync(0xffffffffu, srcv, k * 4 + r4) * ROWB;
            const int lim = rem - r4;
            const int lim6 = svl ? nnodes - q * GRP + 24 - r4 : lim;
            if (svl) { gq[6] = svp; gq[7] = svp + 4 * 512; }
            const uint32_t rxy = hmul2(r.x & 0x9fff9fffu, 0x60806080u);
            const uint32_t rz2 = hmul2(r.y & 0x00009fffu, 0x60806080u);
            const uint32_t qxy = hmul2(rxy, rxy), qz = hmul2(rz2, rz2);
            const float sum = bf16r((__uint_as_float(qxy << 16) + __uint_as_float(qxy & 0xffff0000u)) + __uint_as_float(qz << 16));
            float sq;
            asm("sqrt.approx.ftz.f32 %0, %1;" : "=f"(sq) : "f"(bf16r(sum + 1e-8f)));
            const uint32_t dbits = pack_bf16(0.f, sq);
            float rinv;
            asm("rcp.approx.ftz.f32 %0, %1;" : "=f"(rinv) : "f"(__uint_as_float(dbits)));
            const int di = valid ? max(min((int)(dbits >> 16), DEND - 1) - DBASE, 0) : NTAB - 1;
            const uint4* gp = reinterpret_cast<const uint4*>(di >= HOT0 ? ghot : gcold) + 2 * di;
            const uint4 g0 = gp[0], g1 = gp[1];
            const uint32_t r01 = pack_bf16(__uint_as_float(rxy << 16) * rinv, __uint_as_float(rxy & 0xffff0000u) * rinv);
            const uint32_t r2 = pack_bf16(__uint_as_float(rz2 << 16) * rinv, valid ? 1.0f : 0.f);
            const uint32_t so = ((r.x >> 12) & 6u) | ((r.x >> 26) & 8u);
            const uint32_t fl = last ? (((uint32_t)q << 8) | flast) : 0u;

            const uint32_t bar = sb + ST_CTL;
            mbar_wait(bar + 8, ph);
            const uint32_t dpa = sb + d0, dpb = (dpa ^ 64u) + 512u;
#pragma unroll
            for (int k = 0; k < 8; k++) {
                asm volatile("{\n.reg .pred p;\nsetp.le.s32 p, %2, %3;\n"
                             "cp.async.cg.shared.global [%0], [%1], 16, p;\n"
                             "cp.async.cg.shared.global [%0+4096], [%1+128], 16, p;\n"
                             "cp.async.cg.shared.global [%0+8192], [%1+256], 16, p;\n"
                             "cp.async.cg.shared.global [%0+12288], [%1+384], 16, p;\n}\n"
                             ::"r"(((k & 1) ? dpb : dpa) + (k >> 1) * 1024), "l"(gq[k]), "r"(k < 6 ? lim : lim6), "r"(4 * k) : "memory");
            }
            asm volatile("cp.async.mbarrier.arrive.noinc.shared::cta.b64 [%0];" ::"r"(bar) : "memory");
            const uint32_t za = sb + ST_S + ln * 16;
            asm volatile("st.shared.v4.u32 [%0], {%1,%1,%1,%1};" ::"r"(za), "r"(0u) : "memory");
            asm volatile("st.shared.u16 [%0], %1;" ::"r"(za + so), "h"((unsigned short)(r2 >> 16)) : "memory");
            asm volatile("st.shared.u16 [%0], %1;" ::"r"(sb + roff), "h"((unsigned short)(r01 & 0xffffu)) : "memory");
            asm volatile("st.shared.u16 [%0+64], %1;" ::"r"(sb + roff), "h"((unsigned short)(r01 >> 16)) : "memory");
            asm volatile("st.shared.u16 [%0+128], %1;" ::"r"(sb + roff), "h"((unsigned short)(r2 & 0xffffu)) : "memory");
            asm volatile("st.shared.u32 [%0+16], %1;" ::"r"(bar), "r"(fl) : "memory");
            asm volatile("st.shared.v4.u32 [%0], {%1,%2,%3,%4};" ::"r"(sb + goff),
                         "r"(g0.x), "r"(g0.y), "r"(g0.z), "r"(g0.w) : "memory");
            asm volatile("st.shared.v4.u32 [%0], {%1,%2,%3,%4};" ::"r"((sb + goff) ^ 16u),
                         "r"(g1.x), "r"(g1.y), "r"(g1.z), "r"(g1.w) : "memory");
            asm volatile("fence.proxy.async.shared::cta;" ::: "memory");
            mbar_arrive(bar);
            sb += STAGE_BYTES;
            if (sb == ubase + STAGES * STAGE_BYTES) { sb = ubase; ph ^= 1; }
            rem -= 32;
        } while (!last);
    }
    const uint32_t bar = sb + ST_CTL;
    mbar_wait(bar + 8, ph);
    asm volatile("st.shared.u32 [%0+16], %1;" ::"r"(bar), "r"(8u) : "memory");
    mbar_arrive(bar);
    mbar_arrive(bar);
}

__global__ void __launch_bounds__(M_THREADS, 1)
fused_kernel(const __nv_bfloat16* __restrict__ sv, const __nv_bfloat16* __restrict__ pos,
             const int* __restrict__ src, const int* __restrict__ dst,
             const __nv_bfloat16* __restrict__ freqs, const __nv_bfloat16* __restrict__ w1,
             const __nv_bfloat16* __restrict__ w2, const __nv_bfloat16* __restrict__ wrbf,
             __nv_bfloat16* __restrict__ out, int N, int E) {
    extern __shared__ __align__(1024) unsigned char smem[];
    const int tid = threadIdx.x, lane = tid & 31;
    const int warp = (int)__reduce_or_sync(0xffffffffu, (uint32_t)tid >> 5);
    const uint32_t sbase = smem_u32(smem);
    const uint32_t ghbar = sbase + MS_BAR;
    const bool is_prod = warp >= UNITS * 4;
    const int cta = blockIdx.x;
    const int nnodes = min(NPC, N - cta * NPC);

    STAMP(0, 0);
    unsigned int epoch;
    asm volatile("ld.relaxed.gpu.global.u32 %0, [%1];" : "=r"(epoch) : "l"(&g_cnt));
    unsigned short freq_bits;
    asm volatile("ld.global.nc.u16 %0, [%1];" : "=h"(freq_bits) : "l"(freqs + (tid & 15)));
    const int npair = max(min(EPC, E - cta * EPC), 0) >> 1;
#pragma unroll 1
    for (int i = tid; i < (N * 6 + 15) / 16; i += M_THREADS)
        cp_async16(sbase + PS_POS + i * 16, reinterpret_cast<const unsigned char*>(pos) + i * 16);
    asm volatile("cp.async.commit_group;" ::: "memory");
#pragma unroll 1
    for (int k = 0, i = tid; k < 5; k++, i += M_THREADS) {
        if (i < npair) {
            asm volatile("cp.async.ca.shared.global [%0], [%1], 8;" ::"r"(sbase + PS_SRC + i * 8), "l"(src + cta * EPC + 2 * i) : "memory");
            asm volatile("cp.async.ca.shared.global [%0], [%1], 8;" ::"r"(sbase + PS_DST + i * 8), "l"(dst + cta * EPC + 2 * i) : "memory");
        }
        asm volatile("cp.async.commit_group;" ::: "memory");
    }
    int* hist = reinterpret_cast<int*>(smem + PS_HIST);
    int* b2 = reinterpret_cast<int*>(smem + MS_B2);
    if (tid < 384) {
        reinterpret_cast<int4*>(hist)[tid] = make_int4(0, 0, 0, 0);
        reinterpret_cast<int4*>(b2)[tid] = make_int4(0, 0, 0, 0);
    }
    asm volatile("cp.async.wait_group 5;" ::: "memory");
    __syncthreads();
    STAMP(1, 0);
#pragma unroll 1
    for (int i = tid; i < 96 * 32; i += M_THREADS) {
        const int node = i >> 5, row = node & 31;
        asm volatile("{\n.reg .pred p;\nsetp.ge.s32 p, %2, %3;\ncp.async.cg.shared.global [%0], [%1], 16, p;\n}\n"
                     ::"r"(sbase + (node >> 5) * STAGE_BYTES + (lane >> 3) * 4096 + row * 128 + (((lane ^ row) & 7) << 4)),
                       "l"(sv + (size_t)(cta * NPC + min(node, nnodes - 1)) * 256 + lane * 8), "r"(node), "r"(nnodes) : "memory");
    }
    {
        const int r = tid >> 3, c = tid & 7;
        const uint32_t o = sbase + PS_W1 + r * 128 + (((c ^ r) & 7) << 4);
        cp_async16(o, w1 + tid * 8);
        cp_async16(o + 8192, w2 + r * 192 + 64 + c * 8);
        cp_async16(sbase + PS_W2 + r * 272 + c * 16, w2 + r * 192 + c * 8);
        cp_async16(sbase + PS_W2 + r * 272 + 128 + c * 16, w2 + r * 192 + 128 + c * 8);
        if (tid < 384) cp_async16(sbase + PS_WR + (tid / 24) * 400 + (tid % 24) * 16, wrbf + tid * 8);
    }
    {
        int2* ps = reinterpret_cast<int2*>(smem + PS_SRC);
        int2* pd = reinterpret_cast<int2*>(smem + PS_DST);
        int2* pk = reinterpret_cast<int2*>(smem + PS_KEY);
#pragma unroll 1
        for (int i = tid; i < npair; i += M_THREADS) {
            asm volatile("cp.async.commit_group;\ncp.async.wait_group 5;" ::: "memory");
            const int2 es = ps[i], ed = pd[i];
            int rx[2], ry[2], key[2];
#pragma unroll
            for (int b = 0; b < 2; b++) {
                const uint32_t sn = b ? es.y : es.x, dn = b ? ed.y : ed.x;
                const uint32_t as = sbase + PS_POS + sn * 6, ad = sbase + PS_POS + dn * 6;
                uint32_t sa, sb, da, db;
                asm volatile("ld.shared.u32 %0, [%2];\nld.shared.u32 %1, [%2+4];" : "=r"(sa), "=r"(sb) : "r"(as & ~3u));
                asm volatile("ld.shared.u32 %0, [%2];\nld.shared.u32 %1, [%2+4];" : "=r"(da), "=r"(db) : "r"(ad & ~3u));
                const uint32_t rxy = hsub2(__funnelshift_r(sa, sb, as << 3), __funnelshift_r(da, db, ad << 3));
                const uint32_t rz = hsub2(__funnelshift_r(sb, 0u, as << 3), __funnelshift_r(db, 0u, ad << 3));
                const uint32_t qxy = hmul2(rxy, rxy), qz = hmul2(rz, rz);
                const float sum = (__uint_as_float(qxy << 16) + __uint_as_float(qxy & 0xffff0000u)) + __uint_as_float(qz << 16);
                const uint32_t c = dn / NPC, dl = dn - c * NPC;
                rx[b] = hmul2(rxy, 0x1e801e80u) | ((dl * 0x08002000u) & 0x60006000u);
                ry[b] = __byte_perm(hmul2(rz, 0x1e801e80u), sn, 0x5410) | ((dl * 0x02000200u) & 0x80006000u);
                const uint32_t ba = sbase + PS_HIST + (c * NQ + (dl >> 3)) * 4;
                asm volatile("{\n.reg .pred p;\nsetp.lt.f32 p, %2, 0f41BF8000;\nmov.u32 %0, 0x80000000;\n"
                             "@p atom.shared.add.u32 %0, [%1], 1;\n}\n" : "=r"(key[b]) : "r"(ba), "f"(sum) : "memory");
                key[b] |= ba << 13;
            }
            ps[i] = make_int2(rx[0], rx[1]);
            pd[i] = make_int2(ry[0], ry[1]);
            pk[i] = make_int2(key[0], key[1]);
        }
        STAMP(18, 0);
        asm volatile("cp.async.wait_all;" ::: "memory");
        asm volatile("fence.proxy.async.shared::cta;" ::: "memory");
        __syncthreads();
        STAMP(2, 0);
        if (is_prod) {
            const int pt = tid - UNITS * 128;
            scan1536(hist, pt);
            STAMP(16, 384);
#pragma unroll 1
            for (int gi = cta * 256 + pt; gi < min(cta * 256 + 256, NTAB * NRBF); gi += 128) {
                const float d = __uint_as_float((uint32_t)(DBASE + (gi >> 4)) << 16);
                const float arg = bf16r(d * __uint_as_float((uint32_t)freq_bits << 16));
                float sn;
                if (fabsf(arg) < 1000.f) {
                    const float k = rintf(arg * 0.15915494309189535f);
                    sn = __sinf(fmaf(k, 1.7484556000744883e-7f, fmaf(k, -6.2831854820251465f, arg)));
                } else {
                    sn = sinf(arg);
                }
                const float rbf = bf16r(__fdividef(bf16r(sn), d));
                const float ca = bf16r(bf16r(3.14159265358979f * d) * 0.2f);
                const float fc = 0.5f * bf16r(bf16r(__cosf(ca)) + 1.0f);
                g_G[gi] = __float2bfloat16_rn(rbf * fc);
            }
            if (pt < 2) mbar_init(ghbar + 8 + pt * 8, 128);
            STAMP(17, 384);
        } else {
            const uint32_t tb = sbase + (warp >> 2) * STAGE_BYTES;
            const uint32_t fo = ((lane & 7) + 8 * (lane >> 4)) * 128 + ((uint32_t)((2 * (warp & 3) + ((lane >> 3) & 1)) ^ (lane & 7)) << 4);
            const uint32_t dh = (tb >> 4) | (1u << 16);
            uint32_t x[2][4];
#pragma unroll 1
            for (int it = 0; it < 2; it++) {
                uint32_t a[4][4];
                float d[16];
#pragma unroll
                for (int q = 0; q < 4; q++) ldsm4t(a[q], sbase + PS_W1 + it * 8192 + q * 2048 + fo);
                asm volatile("wgmma.fence.sync.aligned;" ::: "memory");
                wgmma_n32<0, DESC_H>(d, a[0], dh);
                wgmma_n32<1, DESC_H>(d, a[1], dh + 2);
                wgmma_n32<1, DESC_H>(d, a[2], dh + 4);
                wgmma_n32<1, DESC_H>(d, a[3], dh + 6);
                asm volatile("wgmma.commit_group.sync.aligned;" ::: "memory");
                asm volatile("wgmma.wait_group.sync.aligned 0;" ::: "memory");
                reg_fence16(d);
#pragma unroll
                for (int i = 0; i < 8; i++) x[i >> 2][i & 3] = pack_bf16(d[2 * i], d[2 * i + 1]);
                if (it) break;
                asm volatile("bar.sync %0, 128;" ::"r"(1 + (warp >> 2)) : "memory");
#pragma unroll 1
                for (int s = 0; s < 2; s++) {
                    uint32_t y[4];
#pragma unroll
                    for (int e = 0; e < 4; e++) {
                        const float z0 = __uint_as_float(x[0][e] << 16), z1 = __uint_as_float(x[0][e] & 0xffff0000u);
                        float e0, e1;
                        asm("ex2.approx.ftz.f32 %0, %1;" : "=f"(e0) : "f"(z0 * -1.4426950408889634f));
                        asm("ex2.approx.ftz.f32 %0, %1;" : "=f"(e1) : "f"(z1 * -1.4426950408889634f));
                        asm("rcp.approx.ftz.f32 %0, %1;" : "=f"(e0) : "f"(e0 + 1.0f));
                        asm("rcp.approx.ftz.f32 %0, %1;" : "=f"(e1) : "f"(e1 + 1.0f));
                        y[e] = pack_bf16(z0 * e0, z1 * e1);
                        x[0][e] = x[1][e];
                    }
                    stsm4t(tb + fo + s * 2048, y);
                }
                asm volatile("fence.proxy.async.shared::cta;" ::: "memory");
                asm volatile("bar.sync %0, 128;" ::"r"(1 + (warp >> 2)) : "memory");
                STAMP(14, 0);
            }
#pragma unroll 1
            for (int j = 1; j < 4; j++) {
                uint32_t v[2][4];
                ldsm4t(v[0], tb + fo + j * 4096);
                ldsm4t(v[1], tb + fo + j * 4096 + 2048);
#pragma unroll
                for (int e = 0; e < 8; e++) v[e >> 2][e & 3] = hmul2(v[e >> 2][e & 3], x[e >> 2][e & 3]);
                stsm4t(tb + fo + j * 4096, v[0]);
                stsm4t(tb + fo + j * 4096 + 2048, v[1]);
            }
            STAMP(15, 0);
        }
        __syncthreads();
        STAMP(3, 0);
#pragma unroll 2
        for (int node = warp; node < nnodes; node += 16) {
            const int row = node & 31;
            reinterpret_cast<uint4*>(g_tab + (size_t)(cta * NPC + node) * ROWB)[lane] = *reinterpret_cast<const uint4*>(
                smem + (node >> 5) * STAGE_BYTES + (lane >> 3) * 4096 + row * 128 + (((lane ^ row) & 7) << 4));
        }
        STAMP(8, 0);
#pragma unroll 1
        for (int i = tid; i < npair; i += M_THREADS) {
            const int2 k = pk[i], x = ps[i], y = pd[i];
            int o0, o1;
            asm volatile("ld.shared.u32 %0, [%1];" : "=r"(o0) : "r"((k.x >> 13) & 0x3ffff));
            asm volatile("ld.shared.u32 %0, [%1];" : "=r"(o1) : "r"((k.y >> 13) & 0x3ffff));
            int2* sorted = reinterpret_cast<int2*>(smem + PS_POS);
            if (k.x >= 0) sorted[o0 + (k.x & 8191)] = make_int2(x.x, y.x);
            if (k.y >= 0) sorted[o1 + (k.y & 8191)] = make_int2(x.y, y.y);
        }
        __syncthreads();
        STAMP(4, 0);
        const int n16 = (hist[NBIN] + 1) >> 1;
#pragma unroll 1
        for (int i = tid; i < n16; i += M_THREADS)
            reinterpret_cast<uint4*>(g_rec + cta * CH)[i] = reinterpret_cast<const uint4*>(smem + PS_POS)[i];
        __syncthreads();
        STAMP(5, 0);
    }
    const int g = lane >> 2, t = lane & 3;
    unsigned short* pf = reinterpret_cast<unsigned short*>(smem + PS_PF);
    {
        const uint32_t tag = ((epoch / NCTA + 1) & 0xffffu) << 16;
        if (warp < 9) {
            const int c = min(tid >> 1, NCTA - 1);
            const int* h = hist + c * NQ + (tid & 1) * 7;
            uint4 v = make_uint4(h[0] | (h[1] << 16), h[2] | (h[3] << 16), h[4] | (h[5] << 16), h[6] | tag);
            __threadfence();
            asm volatile("st.relaxed.gpu.global.v4.u32 [%0], {%1,%2,%3,%4};" ::"l"(g_pfx + (cta * NCTA + c) * 2 + (tid & 1)),
                         "r"(v.x), "r"(v.y), "r"(v.z), "r"(v.w) : "memory");
        } else if (warp == 15) {
            if (lane < 2 * UNITS * STAGES) mbar_init(sbase + (lane >> 1) * STAGE_BYTES + ST_CTL + (lane & 1) * 8, (lane & 1) ? 4 : 64);
            if (lane == 31) atomicInc(&g_cnt, NCTA * 65536u - 1);
        }
        STAMP(6, 0);
        const int p = min(warp + 16 * (lane >> 1), NCTA - 1);
        uint4 v;
        int spin = 0;
        do {
            asm volatile("ld.acquire.gpu.global.v4.u32 {%0,%1,%2,%3}, [%4];" : "=r"(v.x), "=r"(v.y), "=r"(v.z), "=r"(v.w)
                         : "l"(g_pfx + (p * NCTA + cta) * 2 + (lane & 1)) : "memory");
        } while (__any_sync(0xffffffffu, (v.w ^ tag) & 0xffff0000u) && ++spin < (1 << 22));
        STAMP(7, 0);
        reinterpret_cast<uint4*>(pf)[p * 2 + (lane & 1)] = v;
#pragma unroll 1
        for (int k = 0, pp = warp; pp < NCTA; k += 2, pp += 16) {
            const int i = (__shfl_sync(0xffffffffu, v.x, k) & 0xfffe) + 2 * lane;
            const int e = __shfl_sync(0xffffffffu, v.y, k + 1) >> 16;
            if (i < e) cp_async16(sbase + (3 + (pp >> 5)) * STAGE_BYTES + (pp & 31) * 512 + lane * 16, g_rec + pp * CH + i);
        }
        __syncwarp();
#pragma unroll 1
        for (int e = lane; e < 96; e += 32) {
            const int k = e / NQ, q = e - k * NQ, pp = warp + 16 * k;
            if (pp < NCTA) b2[q * NCTA + pp] = pf[pp * 16 + q + 1 + (q >= 6)] - pf[pp * 16 + q + (q >= 7)];
        }
        __syncthreads();
        STAMP(9, 0);
        if (is_prod) {
            scan1536(b2, tid - UNITS * 128);
        } else {
#pragma unroll 1
            for (int i = tid; i < (NTAB - HOT0) * 2; i += UNITS * 128) cp_async16(sbase + MS_GH + i * 16, g_G + HOT0 * NRBF + i * 8);
        }
        asm volatile("cp.async.wait_all;" ::: "memory");
    }
    __syncthreads();
    STAMP(11, 0);
    if (b2[NBIN] <= RCAP) {
        uint2* srec = reinterpret_cast<uint2*>(smem + MS_REC);
#pragma unroll 1
        for (int p = 2 * warp + (lane >> 4); p < NCTA; p += 32) {
            const int beg = pf[p * 16], end = pf[p * 16 + NQ + 1];
            const uint4* raw = reinterpret_cast<const uint4*>(smem + (3 + (p >> 5)) * STAGE_BYTES + (p & 31) * 512);
#pragma unroll 1
            for (int o = lane & 15, i = (beg & ~1) + 2 * o; i < end; o += 16, i += 32) {
                const uint4 v = o < 32 ? raw[o] : __ldcg(reinterpret_cast<const uint4*>(g_rec + p * CH + i));
                const int q0 = (int)(((v.x >> 30) & 1u) | ((v.y >> 12) & 6u) | ((v.y >> 28) & 8u));
                const int q1 = (int)(((v.z >> 30) & 1u) | ((v.w >> 12) & 6u) | ((v.w >> 28) & 8u));
                if (i >= beg) srec[b2[q0 * NCTA + p] - pf[p * 16 + q0 + (q0 >= 7)] + i] = make_uint2(v.x, v.y);
                if (i + 1 < end) srec[b2[q1 * NCTA + p] - pf[p * 16 + q1 + (q1 >= 7)] + i + 1] = make_uint2(v.z, v.w);
            }
        }
    }
    __syncthreads();
    STAMP(12, 0);

    if (is_prod) {
        asm volatile("setmaxnreg.dec.sync.aligned.u32 80;");
        const int unit = warp - UNITS * 4;
        if (unit < UNITS) {
            asm volatile("bar.sync 6, 480;" ::: "memory");
            STAMP(21, 384);
            if (__reduce_or_sync(0xffffffffu, (uint32_t)b2[NBIN]) <= RCAP) producer_loop<true>(smem, sv, N, unit);
            else producer_loop<false>(smem, sv, N, unit);
            GSTAMP(22 + unit, 384 + 32 * unit);
        }
    } else {
        asm volatile("setmaxnreg.inc.sync.aligned.u32 144;");
        const int unit = warp >> 2, w = warp & 3;
        const uint32_t ubase = sbase + unit * STAGES * STAGE_BYTES;
        uint32_t wa[3][4], pa[2][4][4];
        {
            const int krow = (lane & 7) + 8 * (lane >> 4), mcol = 2 * w + ((lane >> 3) & 1);
#pragma unroll
            for (int q = 0; q < 4; q++) {
                ldsm4t(pa[0][q], sbase + PS_W2 + (16 * q + krow) * 272 + mcol * 16);
                ldsm4t(pa[1][q], sbase + PS_W2 + (16 * q + krow) * 272 + 128 + mcol * 16);
            }
#pragma unroll
            for (int p = 0; p < 3; p++) ldsm4t(wa[p], sbase + PS_WR + krow * 400 + p * 128 + mcol * 16);
            asm volatile("bar.arrive 6, 480;" ::: "memory");
        }
        float acc[4][4];
#pragma unroll
        for (int c = 0; c < 4; c++)
#pragma unroll
            for (int e = 0; e < 4; e++) acc[c][e] = 0.f;
        const int erow = (lane & 7) + 8 * (lane >> 4);
        const int ehalf = (lane >> 3) & 1;
        const uint32_t ua = pin(4096 + erow * 128 + ((uint32_t)((2 * w + ehalf) ^ (lane & 7)) << 4));
        const uint32_t sa = pin(ST_S + lane * 16);
        const uint32_t ra = pin(ST_R + t * 16);
        const uint32_t ub = __reduce_or_sync(0xffffffffu, ubase);
        uint32_t sb = ub;
        uint32_t ph = 0;
        const bool elected = sa == ST_S;
        while (true) {
            mbar_wait(sb + ST_CTL, ph);
            {
                const uint32_t dh = (sb >> 4) | (1u << 16);
                const uint32_t dg = dh + (ST_G >> 4);
                uint32_t m[2][4], wv[2][4], u[3][4], sf[4], rr[3][2];
                float p0[16], f0[16], fv[16];
                asm volatile("wgmma.fence.sync.aligned;" ::: "memory");
                wgmma_n32<0, DESC_G>(f0, wa[2], dg);
                wgmma_n32<0, DESC_H>(p0, pa[1][0], dh);
                wgmma_n32<1, DESC_H>(p0, pa[1][1], dh + 2);
                wgmma_n32<1, DESC_H>(p0, pa[1][2], dh + 4);
                wgmma_n32<1, DESC_H>(p0, pa[1][3], dh + 6);
                wgmma_n32<0, DESC_G>(fv, wa[1], dg);
                asm volatile("wgmma.commit_group.sync.aligned;" ::: "memory");
#pragma unroll
                for (int j = 0; j < 3; j++) {
                    ldsm4t(u[j], sb + ua + j * 4096);
                    asm volatile("ld.shared.v2.u32 {%0,%1}, [%2];" : "=r"(rr[j][0]), "=r"(rr[j][1]) : "r"(sb + ra + j * 64));
                }
                ldsm4t(sf, sb + sa);
                asm volatile("wgmma.wait_group.sync.aligned 0;" ::: "memory");
                reg_fence16(fv); reg_fence16(f0); reg_fence16(p0);
#pragma unroll
                for (int i = 0; i < 8; i++) {
                    m[i >> 2][i & 3] = pack_bf16(f0[2 * i] * p0[2 * i], f0[2 * i + 1] * p0[2 * i + 1]);
                    wv[i >> 2][i & 3] = pack_bf16(fv[2 * i], fv[2 * i + 1]);
                }
                asm volatile("wgmma.fence.sync.aligned;" ::: "memory");
                wgmma_n32<0, DESC_G>(f0, wa[0], dg);
                wgmma_n32<0, DESC_H>(p0, pa[0][0], dh);
                wgmma_n32<1, DESC_H>(p0, pa[0][1], dh + 2);
                wgmma_n32<1, DESC_H>(p0, pa[0][2], dh + 4);
                wgmma_n32<1, DESC_H>(p0, pa[0][3], dh + 6);
                asm volatile("wgmma.commit_group.sync.aligned;" ::: "memory");
                uint32_t v1[3][4];
#pragma unroll
                for (int j = 0; j < 3; j++)
#pragma unroll
                    for (int e = 0; e < 4; e++) u[j][e] = hfma2(m[0][e], rr[j][e >> 1], hmul2(u[j][e], wv[0][e]));
#pragma unroll
                for (int j = 0; j < 3; j++) {
                    ldsm4t(v1[j], sb + ua + j * 4096 + 2048);
                    asm volatile("ld.shared.v2.u32 {%0,%1}, [%2];" : "=r"(rr[j][0]), "=r"(rr[j][1]) : "r"(sb + ra + j * 64 + 8));
                }
#pragma unroll
                for (int j = 0; j < 3; j++)
#pragma unroll
                    for (int e = 0; e < 4; e++) v1[j][e] = hfma2(m[1][e], rr[j][e >> 1], hmul2(v1[j][e], wv[1][e]));
#pragma unroll
                for (int j = 0; j < 3; j++) mma16816(acc[j + 1], u[j], sf[0], sf[1]);
#pragma unroll
                for (int j = 0; j < 3; j++) mma16816(acc[j + 1], v1[j], sf[2], sf[3]);
                asm volatile("wgmma.wait_group.sync.aligned 0;" ::: "memory");
                reg_fence16(f0); reg_fence16(p0);
#pragma unroll
                for (int i = 0; i < 8; i++)
                    m[i >> 2][i & 3] = pack_bf16(f0[2 * i] * p0[2 * i], f0[2 * i + 1] * p0[2 * i + 1]);
                mma16816(acc[0], m[0], sf[0], sf[1]);
                mma16816(acc[0], m[1], sf[2], sf[3]);
            }
            uint32_t flags;
            asm volatile("ld.shared.u32 %0, [%1+16];" : "=r"(flags) : "r"(sb + ST_CTL));
            if (flags) {
                if (flags & 8u) break;
                float* part = reinterpret_cast<float*>(smem + MS_PART) + (tid & 127);
                if (flags & 4u) {
#pragma unroll
                    for (int i = 0; i < 16; i++) part[(unit - 1) * 2048 + i * 128] = acc[i >> 2][i & 3];
                    mbar_arrive(sbase + MS_BAR + unit * 8);
                } else {
#pragma unroll 1
                    for (int k = 0; k < 2; k++) {
                        if (flags & (16u << k)) {
                            mbar_wait(sbase + MS_BAR + 8 + k * 8, 0);
#pragma unroll
                            for (int i = 0; i < 16; i++) acc[i >> 2][i & 3] += part[k * 2048 + i * 128];
                        }
                    }
                    const uint32_t ea = sb + (lane >> 4) * 4096 + (24 + (lane & 7)) * 128 +
                                        ((uint32_t)((2 * w + ((lane >> 3) & 1)) ^ (lane & 7)) << 4);
#pragma unroll
                    for (int k = 0; k < 2; k++) {
                        uint32_t v[4];
                        ldsm4t(v, ea + k * 8192);
#pragma unroll
                        for (int e = 0; e < 4; e++)
                            v[e] = pack_bf16(__uint_as_float(v[e] << 16) + acc[2 * k + (e >> 1)][2 * (e & 1)],
                                             __uint_as_float(v[e] & 0xffff0000u) + acc[2 * k + (e >> 1)][2 * (e & 1) + 1]);
                        stsm4t(ea + k * 8192, v);
                    }
                    __syncwarp();
                    const int ln0 = (int)(flags >> 8) * GRP + (lane >> 2);
                    const int c0 = (lane >> 1) & 1, ch = 2 * w + (lane & 1);
                    uint4* op = reinterpret_cast<uint4*>(out + (size_t)(blockIdx.x * NPC + ln0) * 256) + c0 * 8 + ch;
                    const uint32_t ia = sb + c0 * 4096 + (24 + (lane >> 2)) * 128 + ((uint32_t)(ch ^ (lane >> 2)) << 4);
#pragma unroll
                    for (int k = 0; k < 2; k++) {
                        asm volatile("{\n.reg .pred p;\n.reg .b32 a, b, c, d;\nsetp.lt.s32 p, %2, %3;\n"
                                     "ld.shared.v4.u32 {a, b, c, d}, [%0];\n"
                                     "@p st.global.v4.u32 [%1], {a, b, c, d};\n}\n"
                                     ::"r"(ia + k * 8192), "l"(op + k * 16), "r"(ln0), "r"(min(NPC, N - (int)blockIdx.x * NPC)) : "memory");
                    }
                }
#pragma unroll
                for (int i = 0; i < 16; i++) acc[i >> 2][i & 3] = 0.f;
            }
            __syncwarp();
            if (elected) mbar_arrive(sb + ST_CTL + 8);
            sb += STAGE_BYTES;
            if (sb == ub + STAGES * STAGE_BYTES) { sb = ub; ph ^= 1; }
        }
        GSTAMP(26 + unit, 128 * unit);
    }
}

}

extern "C" void kernel_launch(void* const* d_in, const int* in_sizes, int n_in, void* d_out, int out_size) {
    const __nv_bfloat16* sv = (const __nv_bfloat16*)d_in[0];
    const __nv_bfloat16* pos = (const __nv_bfloat16*)d_in[1];
    const int* src = (const int*)d_in[2];
    const int* dst = (const int*)d_in[3];
    const __nv_bfloat16* freqs = (const __nv_bfloat16*)d_in[4];
    const __nv_bfloat16* w1 = (const __nv_bfloat16*)d_in[5];
    const __nv_bfloat16* w2 = (const __nv_bfloat16*)d_in[6];
    const __nv_bfloat16* wrbf = (const __nv_bfloat16*)d_in[7];
    __nv_bfloat16* out = (__nv_bfloat16*)d_out;
    const int N = in_sizes[1] / 3;
    const int E = in_sizes[2];

    static bool init = false;
    if (!init) {
        cudaFuncSetAttribute(fused_kernel, cudaFuncAttributeMaxDynamicSharedMemorySize, M_SMEM);
        init = true;
    }
    fused_kernel<<<NCTA, M_THREADS, M_SMEM, cudaStreamPerThread>>>(sv, pos, src, dst, freqs, w1, w2, wrbf, out, N, E);
}
```

```cpp
#include <cuda_runtime.h>
#include <cuda_bf16.h>
#include <stdint.h>

namespace {

constexpr int D = 64;
constexpr int NRBF = 16;
constexpr int MAXN = 10000;
constexpr int MAXE = 640000;
constexpr int NCTA = 132;
constexpr int GRP = 8;
constexpr int NPC = (MAXN + NCTA - 1) / NCTA;
constexpr int NQ = (NPC + GRP - 1) / GRP;
constexpr int NBIN = NCTA * NQ;
constexpr int CH = 4864;
constexpr int DBASE = 0x38C0;
constexpr int DEND = 0x40A0;
constexpr int NTAB = DEND - DBASE;
constexpr int ROWB = 512;

__device__ __align__(128) unsigned char g_tab[(size_t)(MAXN + 16) * ROWB];
__device__ __align__(128) __nv_bfloat16 g_G[NTAB * NRBF];
__device__ __align__(128) uint2 g_rec[NCTA * CH];
__device__ __align__(128) uint4 g_pfx[NCTA * NCTA * 2];
__device__ unsigned int g_cnt;

#define STAMP(k, tt) do {} while (0)
#define GSTAMP(k, tt) do {} while (0)

__device__ __forceinline__ uint32_t smem_u32(const void* p) { return (uint32_t)__cvta_generic_to_shared(p); }
__device__ __forceinline__ uint32_t pack_bf16(float lo, float hi) {
    uint32_t r;
    asm("cvt.rn.bf16x2.f32 %0, %1, %2;" : "=r"(r) : "f"(hi), "f"(lo));
    return r;
}
__device__ __forceinline__ float bf16r(float x) { return __uint_as_float(pack_bf16(0.f, x) & 0xffff0000u); }
__device__ __forceinline__ uint32_t hmul2(uint32_t a, uint32_t b) {
    uint32_t r;
    asm("mul.rn.bf16x2 %0, %1, %2;" : "=r"(r) : "r"(a), "r"(b));
    return r;
}
__device__ __forceinline__ uint32_t hsub2(uint32_t a, uint32_t b) {
    uint32_t r;
    asm("sub.rn.bf16x2 %0, %1, %2;" : "=r"(r) : "r"(a), "r"(b));
    return r;
}
__device__ __forceinline__ uint32_t hfma2(uint32_t a, uint32_t b, uint32_t c) {
    uint32_t r;
    asm("fma.rn.bf16x2 %0, %1, %2, %3;" : "=r"(r) : "r"(a), "r"(b), "r"(c));
    return r;
}
__device__ __forceinline__ void mma16816(float (&c)[4], const uint32_t (&a)[4], uint32_t b0, uint32_t b1) {
    asm volatile("mma.sync.aligned.m16n8k16.row.col.f32.bf16.bf16.f32 {%0,%1,%2,%3}, {%4,%5,%6,%7}, {%8,%9}, {%0,%1,%2,%3};"
                 : "+f"(c[0]), "+f"(c[1]), "+f"(c[2]), "+f"(c[3])
                 : "r"(a[0]), "r"(a[1]), "r"(a[2]), "r"(a[3]), "r"(b0), "r"(b1));
}
__device__ __forceinline__ void mma16816_z(float (&c)[4], const uint32_t (&a)[4], uint32_t b0, uint32_t b1) {
    asm volatile("mma.sync.aligned.m16n8k16.row.col.f32.bf16.bf16.f32 {%0,%1,%2,%3}, {%4,%5,%6,%7}, {%8,%9}, {%10,%10,%10,%10};"
                 : "=f"(c[0]), "=f"(c[1]), "=f"(c[2]), "=f"(c[3])
                 : "r"(a[0]), "r"(a[1]), "r"(a[2]), "r"(a[3]), "r"(b0), "r"(b1), "f"(0.f));
}
__device__ __forceinline__ void ldsm4(uint32_t (&r)[4], uint32_t addr) {
    asm volatile("ldmatrix.sync.aligned.m8n8.x4.shared.b16 {%0,%1,%2,%3}, [%4];"
                 : "=r"(r[0]), "=r"(r[1]), "=r"(r[2]), "=r"(r[3]) : "r"(addr));
}
__device__ __forceinline__ void ldsm4t(uint32_t (&r)[4], uint32_t addr) {
    asm volatile("ldmatrix.sync.aligned.m8n8.x4.trans.shared.b16 {%0,%1,%2,%3}, [%4];"
                 : "=r"(r[0]), "=r"(r[1]), "=r"(r[2]), "=r"(r[3]) : "r"(addr));
}
__device__ __forceinline__ void stsm4t(uint32_t addr, const uint32_t (&r)[4]) {
    asm volatile("stmatrix.sync.aligned.m8n8.x4.trans.shared.b16 [%0], {%1,%2,%3,%4};"
                 ::"r"(addr), "r"(r[0]), "r"(r[1]), "r"(r[2]), "r"(r[3]) : "memory");
}
__device__ __forceinline__ void cp_async16(uint32_t dst, const void* src) {
    asm volatile("cp.async.cg.shared.global [%0], [%1], 16;" ::"r"(dst), "l"(src) : "memory");
}
__device__ __forceinline__ void mbar_init(uint32_t bar, int cnt) {
    asm volatile("mbarrier.init.shared::cta.b64 [%0], %1;" ::"r"(bar), "r"(cnt) : "memory");
}
__device__ __forceinline__ void mbar_arrive(uint32_t bar) {
    asm volatile("mbarrier.arrive.shared::cta.b64 _, [%0];" ::"r"(bar) : "memory");
}
__device__ __forceinline__ void mbar_expect_tx(uint32_t bar, uint32_t bytes) {
    asm volatile("mbarrier.arrive.expect_tx.shared::cta.b64 _, [%0], %1;" ::"r"(bar), "r"(bytes) : "memory");
}
__device__ __forceinline__ void mbar_wait(uint32_t bar, uint32_t parity) {
    asm volatile(
        "{\n.reg .pred p;\n.reg .u32 n;\nmov.u32 n, 0;\n"
        "WAIT_%=:\n"
        "mbarrier.try_wait.parity.shared::cta.b64 p, [%0], %1, %2;\n"
        "@p bra DONE_%=;\n"
        "add.u32 n, n, 1;\n"
        "setp.lt.u32 p, n, 100000;\n"
        "@p bra WAIT_%=;\n"
        "exit;\n"
        "DONE_%=:\n}\n" ::"r"(bar), "r"(parity), "r"(10000u) : "memory");
}
__device__ __forceinline__ void bulk_g2s(uint32_t dst, const void* src, uint32_t bytes, uint32_t bar) {
    asm volatile("cp.async.bulk.shared::cluster.global.mbarrier::complete_tx::bytes [%0], [%1], %2, [%3];"
                 ::"r"(dst), "l"(src), "r"(bytes), "r"(bar) : "memory");
}
__device__ __forceinline__ void bulk_s2g(void* dst, uint32_t src, uint32_t bytes) {
    asm volatile("cp.async.bulk.global.shared::cta.bulk_group [%0], [%1], %2;" ::"l"(dst), "r"(src), "r"(bytes) : "memory");
}

constexpr int UNITS = 3;
constexpr int STAGES = 3;
constexpr int M_THREADS = UNITS * 128 + 128;
constexpr int ST_G = 4 * 4096;
constexpr int ST_S = ST_G + 1024;
constexpr int ST_R = ST_S + 512;
constexpr int ST_CTL = ST_R + 192;
constexpr int STAGE_BYTES = ST_S + 1024;
constexpr int RCAP = 3776;
constexpr int HOT0 = 0x3F00 - DBASE;
constexpr int MS_REC = UNITS * STAGES * STAGE_BYTES;
constexpr int MS_PART = MS_REC + RCAP * 8;
constexpr int MS_GH = MS_PART + 2 * 8192;
constexpr int MS_B2 = MS_GH + (NTAB - HOT0) * 32;
constexpr int MS_MISC = MS_B2 + 1536 * 4;
constexpr int MS_BAR = MS_MISC + 32 * 4;
constexpr int MS_DBG = MS_BAR + 64;
constexpr int M_SMEM = MS_DBG + 256;
constexpr int EPC = 4852;
constexpr int PS_POS = UNITS * STAGE_BYTES;
constexpr int PS_W1 = PS_POS + 60032;
constexpr int PS_WR = 7 * STAGE_BYTES + 4096;
constexpr int PS_HIST = PS_WR + 16 * 400;
constexpr int PS_W2 = 8 * STAGE_BYTES;
constexpr int PS_SRC = MS_REC;
constexpr int PS_DST = PS_SRC + CH * 4;
constexpr int PS_KEY = PS_DST + CH * 4;
constexpr int PS_PF = MS_PART;
static_assert(PS_W1 % 128 == 0 && PS_W1 + 16384 <= PS_WR && PS_HIST + (1536 + 32) * 4 <= 7 * STAGE_BYTES + ST_CTL &&
              64 * 272 <= ST_CTL && PS_KEY + CH * 4 <= MS_B2 && EPC * NCTA >= MAXE && EPC <= CH && CH * 8 <= 60032,
              "phase-1 layout");
static_assert(M_SMEM <= 232448, "smem");
static_assert(MS_BAR % 8 == 0 && MS_GH % 16 == 0 && STAGE_BYTES % 1024 == 0, "align");

template <int ACC, uint32_t HI>
__device__ __forceinline__ void wgmma_n32(float (&d)[16], const uint32_t (&a)[4], uint32_t lo) {
    if (ACC) {
        asm volatile("{\n.reg .b64 dd;\nmov.b64 dd, {%20, %21};\n"
                     "wgmma.mma_async.sync.aligned.m64n32k16.f32.bf16.bf16 {%0,%1,%2,%3,%4,%5,%6,%7,%8,%9,%10,%11,%12,%13,%14,%15}, {%16,%17,%18,%19}, dd, 1, 1, 1, 0;\n}\n"
                     : "+f"(d[0]), "+f"(d[1]), "+f"(d[2]), "+f"(d[3]), "+f"(d[4]), "+f"(d[5]), "+f"(d[6]), "+f"(d[7]),
                       "+f"(d[8]), "+f"(d[9]), "+f"(d[10]), "+f"(d[11]), "+f"(d[12]), "+f"(d[13]), "+f"(d[14]), "+f"(d[15])
                     : "r"(a[0]), "r"(a[1]), "r"(a[2]), "r"(a[3]), "r"(lo), "n"(HI));
    } else {
        asm volatile("{\n.reg .b64 dd;\nmov.b64 dd, {%20, %21};\n"
                     "wgmma.mma_async.sync.aligned.m64n32k16.f32.bf16.bf16 {%0,%1,%2,%3,%4,%5,%6,%7,%8,%9,%10,%11,%12,%13,%14,%15}, {%16,%17,%18,%19}, dd, 0, 1, 1, 0;\n}\n"
                     : "=f"(d[0]), "=f"(d[1]), "=f"(d[2]), "=f"(d[3]), "=f"(d[4]), "=f"(d[5]), "=f"(d[6]), "=f"(d[7]),
                       "=f"(d[8]), "=f"(d[9]), "=f"(d[10]), "=f"(d[11]), "=f"(d[12]), "=f"(d[13]), "=f"(d[14]), "=f"(d[15])
                     : "r"(a[0]), "r"(a[1]), "r"(a[2]), "r"(a[3]), "r"(lo), "n"(HI));
    }
}
constexpr uint32_t DESC_H = 64u | (1u << 30);
constexpr uint32_t DESC_G = 16u | (3u << 30);
__device__ __forceinline__ void reg_fence16(float (&d)[16]) {
    asm volatile("" : "+f"(d[0]), "+f"(d[1]), "+f"(d[2]), "+f"(d[3]), "+f"(d[4]), "+f"(d[5]), "+f"(d[6]), "+f"(d[7]),
                      "+f"(d[8]), "+f"(d[9]), "+f"(d[10]), "+f"(d[11]), "+f"(d[12]), "+f"(d[13]), "+f"(d[14]), "+f"(d[15]) :: "memory");
}
__device__ __forceinline__ uint32_t pin(uint32_t x) { return __shfl_sync(0xffffffffu, x, threadIdx.x & 31); }

__device__ __forceinline__ void scan1536(int* h, int pt) {
    int4* h4 = reinterpret_cast<int4*>(h) + pt * 3;
    int4 a = h4[0], b = h4[1], c = h4[2];
    a.y += a.x; a.z += a.y; a.w += a.z; b.x += a.w; b.y += b.x; b.z += b.y; b.w += b.z;
    c.x += b.w; c.y += c.x; c.z += c.y; c.w += c.z;
    int incl = c.w;
#pragma unroll
    for (int o = 1; o < 32; o <<= 1) {
        const int v = __shfl_up_sync(0xffffffffu, incl, o);
        if ((pt & 31) >= o) incl += v;
    }
    if ((pt & 31) == 31) h[1536 + (pt >> 5)] = incl;
    asm volatile("bar.sync 4, 128;" ::: "memory");
    const int ex = __reduce_add_sync(0xffffffffu, (pt & 31) < (pt >> 5) ? h[1536 + (pt & 31)] : 0) + incl - c.w;
    h4[0] = make_int4(ex, ex + a.x, ex + a.y, ex + a.z);
    h4[1] = make_int4(ex + a.w, ex + b.x, ex + b.y, ex + b.z);
    h4[2] = make_int4(ex + b.w, ex + c.x, ex + c.y, ex + c.z);
}

template <bool FITS>
__device__ __forceinline__ void producer_loop(unsigned char* smem, const __nv_bfloat16* __restrict__ sv, int N, int unit) {
    const uint32_t sbase = smem_u32(smem);
    const uint32_t ubase = __reduce_or_sync(0xffffffffu, sbase + unit * STAGES * STAGE_BYTES);
    const int* b2 = reinterpret_cast<const int*>(smem + MS_B2);
    const int ln = pin(threadIdx.x & 31);
    const int r4 = ln >> 3;
    const unsigned char* gsrc = g_tab + (ln & 7) * 16;
    asm volatile("" : "+l"(gsrc));
    const uint32_t d0 = r4 * 128 + (((ln & 7) ^ r4) << 4);
    const uint32_t goff = ST_G + ln * 32 + (((ln >> 2) & 1) << 4);
    const uint32_t roff = ST_R + ((ln >> 1) & 3) * 16 + (ln >> 3) * 4 + (ln & 1) * 2;
    const unsigned char* ghot = smem + (MS_GH - HOT0 * 32);
    const unsigned char* gcold = reinterpret_cast<const unsigned char*>(g_G);
    asm volatile("" : "+l"(ghot), "+l"(gcold));
    uint32_t sb = ubase, ph = 1;
    const int total = (int)__reduce_or_sync(0xffffffffu, (uint32_t)b2[NBIN]);
    const int s1 = total / 3, s2 = (2 * total) / 3;
    const int un = (int)__reduce_or_sync(0xffffffffu, (uint32_t)unit);
    const int ulo = un == 0 ? 0 : (un == 1 ? s1 : s2);
    const int uhi = un == 0 ? s1 : (un == 1 ? s2 : total);
    const int nnodes = min(NPC, N - (int)blockIdx.x * NPC);
    int gb = 0;
    for (int q = 0; q < NQ; q++) {
        const int ge = (int)__reduce_or_sync(0xffffffffu, (uint32_t)b2[(q + 1) * NCTA]);
        const int beg = gb;
        gb = ge;
        const bool own = beg >= ulo && (beg < uhi || un == 2);
        const int lo = max(beg, ulo), hi = min(ge, uhi);
        if (!own && lo >= hi) continue;
        uint32_t ra = sbase + MS_REC + (lo + ln) * 8;
        int rem = max(hi - lo, 0);
        const int lastcap = own ? 24 : 32;
        uint32_t flast = own ? 2u : 4u;
        if (own && un == 0 && beg < s1 && s1 < ge && s1 < s2) flast |= 16u;
        if (own && un < 2 && beg < s2 && s2 < ge) flast |= 32u;
        const unsigned char* svp = reinterpret_cast<const unsigned char*>(sv) +
                                   (size_t)(blockIdx.x * NPC + q * GRP + r4) * 512 + (ln & 7) * 16;
        auto fetch = [&](int left) -> uint2 {
            uint2 r = make_uint2(0, 0);
            if (FITS) {
                asm volatile("ld.shared.v2.u32 {%0,%1}, [%2];" : "=r"(r.x), "=r"(r.y) : "r"(ra));
                ra += 256;
            } else if (ln < left) {
                const int j = hi - left + ln;
                const int* prq = b2 + q * NCTA;
                int lo = 0, up = NCTA;
                while (up - lo > 1) {
                    const int mid = (lo + up) >> 1;
                    if (prq[mid] <= j) lo = mid; else up = mid;
                }
                const int b0 = __ldcg(reinterpret_cast<const unsigned short*>(g_pfx + (lo * NCTA + blockIdx.x) * 2) + q + (q >= 7));
                r = __ldcg(g_rec + lo * CH + b0 + (j - prq[lo]));
            }
            return r;
        };
        uint2 rn = fetch(rem);
        bool last;
        do {
            const bool valid = ln < rem;
            last = rem <= lastcap;
            const bool svl = last && own;
            const uint2 r = valid ? rn : make_uint2(0, 0);
            rn = fetch(rem - 32);
            const uint32_t srcv = (r.y >> 16) & 0x7fffu;
            const unsigned char* gq[8];
#pragma unroll
            for (int k = 0; k < 8; k++)
                gq[k] = gsrc + (size_t)__shfl_sync(0xffffffffu, srcv, k * 4 + r4) * ROWB;
            const int lim = rem - r4;
            const int lim6 = svl ? nnodes - q * GRP + 24 - r4 : lim;
            if (svl) { gq[6] = svp; gq[7] = svp + 4 * 512; }
            const uint32_t rxy = hmul2(r.x & 0x9fff9fffu, 0x60806080u);
            const uint32_t rz2 = hmul2(r.y & 0x00009fffu, 0x60806080u);
            const uint32_t qxy = hmul2(rxy, rxy), qz = hmul2(rz2, rz2);
            const float sum = bf16r((__uint_as_float(qxy << 16) + __uint_as_float(qxy & 0xffff0000u)) + __uint_as_float(qz << 16));
            float sq;
            asm("sqrt.approx.ftz.f32 %0, %1;" : "=f"(sq) : "f"(bf16r(sum + 1e-8f)));
            const uint32_t dbits = pack_bf16(0.f, sq);
            float rinv;
            asm("rcp.approx.ftz.f32 %0, %1;" : "=f"(rinv) : "f"(__uint_as_float(dbits)));
            const int di = valid ? max(min((int)(dbits >> 16), DEND - 1) - DBASE, 0) : NTAB - 1;
            const uint4* gp = reinterpret_cast<const uint4*>(di >= HOT0 ? ghot : gcold) + 2 * di;
            const uint4 g0 = gp[0], g1 = gp[1];
            const uint32_t r01 = pack_bf16(__uint_as_float(rxy << 16) * rinv, __uint_as_float(rxy & 0xffff0000u) * rinv);
            const uint32_t r2 = pack_bf16(__uint_as_float(rz2 << 16) * rinv, valid ? 1.0f : 0.f);
            const uint32_t so = ((r.x >> 12) & 6u) | ((r.x >> 26) & 8u);
            const uint32_t fl = last ? (((uint32_t)q << 8) | flast) : 0u;

            const uint32_t bar = sb + ST_CTL;
            mbar_wait(bar + 8, ph);
            const uint32_t dpa = sb + d0, dpb = (dpa ^ 64u) + 512u;
#pragma unroll
            for (int k = 0; k < 8; k++) {
                asm volatile("{\n.reg .pred p;\nsetp.le.s32 p, %2, %3;\n"
                             "cp.async.cg.shared.global [%0], [%1], 16, p;\n"
                             "cp.async.cg.shared.global [%0+4096], [%1+128], 16, p;\n"
                             "cp.async.cg.shared.global [%0+8192], [%1+256], 16, p;\n"
                             "cp.async.cg.shared.global [%0+12288], [%1+384], 16, p;\n}\n"
                             ::"r"(((k & 1) ? dpb : dpa) + (k >> 1) * 1024), "l"(gq[k]), "r"(k < 6 ? lim : lim6), "r"(4 * k) : "memory");
            }
            asm volatile("cp.async.mbarrier.arrive.noinc.shared::cta.b64 [%0];" ::"r"(bar) : "memory");
            const uint32_t za = sb + ST_S + ln * 16;
            asm volatile("st.shared.v4.u32 [%0], {%1,%1,%1,%1};" ::"r"(za), "r"(0u) : "memory");
            asm volatile("st.shared.u16 [%0], %1;" ::"r"(za + so), "h"((unsigned short)(r2 >> 16)) : "memory");
            asm volatile("st.shared.u16 [%0], %1;" ::"r"(sb + roff), "h"((unsigned short)(r01 & 0xffffu)) : "memory");
            asm volatile("st.shared.u16 [%0+64], %1;" ::"r"(sb + roff), "h"((unsigned short)(r01 >> 16)) : "memory");
            asm volatile("st.shared.u16 [%0+128], %1;" ::"r"(sb + roff), "h"((unsigned short)(r2 & 0xffffu)) : "memory");
            asm volatile("st.shared.u32 [%0+16], %1;" ::"r"(bar), "r"(fl) : "memory");
            asm volatile("st.shared.v4.u32 [%0], {%1,%2,%3,%4};" ::"r"(sb + goff),
                         "r"(g0.x), "r"(g0.y), "r"(g0.z), "r"(g0.w) : "memory");
            asm volatile("st.shared.v4.u32 [%0], {%1,%2,%3,%4};" ::"r"((sb + goff) ^ 16u),
                         "r"(g1.x), "r"(g1.y), "r"(g1.z), "r"(g1.w) : "memory");
            asm volatile("fence.proxy.async.shared::cta;" ::: "memory");
            mbar_arrive(bar);
            sb += STAGE_BYTES;
            if (sb == ubase + STAGES * STAGE_BYTES) { sb = ubase; ph ^= 1; }
            rem -= 32;
        } while (!last);
    }
    const uint32_t bar = sb + ST_CTL;
    mbar_wait(bar + 8, ph);
    asm volatile("st.shared.u32 [%0+16], %1;" ::"r"(bar), "r"(8u) : "memory");
    mbar_arrive(bar);
    mbar_arrive(bar);
}

__global__ void __launch_bounds__(M_THREADS, 1)
fused_kernel(const __nv_bfloat16* __restrict__ sv, const __nv_bfloat16* __restrict__ pos,
             const int* __restrict__ src, const int* __restrict__ dst,
             const __nv_bfloat16* __restrict__ freqs, const __nv_bfloat16* __restrict__ w1,
             const __nv_bfloat16* __restrict__ w2, const __nv_bfloat16* __restrict__ wrbf,
             __nv_bfloat16* __restrict__ out, int N, int E) {
    extern __shared__ __align__(1024) unsigned char smem[];
    const int tid = threadIdx.x, lane = tid & 31;
    const int warp = (int)__reduce_or_sync(0xffffffffu, (uint32_t)tid >> 5);
    const uint32_t sbase = smem_u32(smem);
    const uint32_t ghbar = sbase + MS_BAR;
    const bool is_prod = warp >= UNITS * 4;
    const int cta = blockIdx.x;
    const int nnodes = min(NPC, N - cta * NPC);

    STAMP(0, 0);
    unsigned int epoch;
    asm volatile("ld.relaxed.gpu.global.u32 %0, [%1];" : "=r"(epoch) : "l"(&g_cnt));
    unsigned short freq_bits;
    asm volatile("ld.global.nc.u16 %0, [%1];" : "=h"(freq_bits) : "l"(freqs + (tid & 15)));
    const int npair = max(min(EPC, E - cta * EPC), 0) >> 1;
#pragma unroll 1
    for (int i = tid; i < (N * 6 + 15) / 16; i += M_THREADS)
        cp_async16(sbase + PS_POS + i * 16, reinterpret_cast<const unsigned char*>(pos) + i * 16);
    asm volatile("cp.async.commit_group;" ::: "memory");
#pragma unroll 1
    for (int k = 0, i = tid; k < 5; k++, i += M_THREADS) {
        if (i < npair) {
            asm volatile("cp.async.ca.shared.global [%0], [%1], 8;" ::"r"(sbase + PS_SRC + i * 8), "l"(src + cta * EPC + 2 * i) : "memory");
            asm volatile("cp.async.ca.shared.global [%0], [%1], 8;" ::"r"(sbase + PS_DST + i * 8), "l"(dst + cta * EPC + 2 * i) : "memory");
        }
        asm volatile("cp.async.commit_group;" ::: "memory");
    }
    int* hist = reinterpret_cast<int*>(smem + PS_HIST);
    int* b2 = reinterpret_cast<int*>(smem + MS_B2);
    if (tid < 384) {
        reinterpret_cast<int4*>(hist)[tid] = make_int4(0, 0, 0, 0);
        reinterpret_cast<int4*>(b2)[tid] = make_int4(0, 0, 0, 0);
    }
    asm volatile("cp.async.wait_group 5;" ::: "memory");
    __syncthreads();
    STAMP(1, 0);
#pragma unroll 1
    for (int i = tid; i < 96 * 32; i += M_THREADS) {
        const int node = i >> 5, row = node & 31;
        asm volatile("{\n.reg .pred p;\nsetp.ge.s32 p, %2, %3;\ncp.async.cg.shared.global [%0], [%1], 16, p;\n}\n"
                     ::"r"(sbase + (node >> 5) * STAGE_BYTES + (lane >> 3) * 4096 + row * 128 + (((lane ^ row) & 7) << 4)),
                       "l"(sv + (size_t)(cta * NPC + min(node, nnodes - 1)) * 256 + lane * 8), "r"(node), "r"(nnodes) : "memory");
    }
    {
        const int r = tid >> 3, c = tid & 7;
        const uint32_t o = sbase + PS_W1 + r * 128 + (((c ^ r) & 7) << 4);
        cp_async16(o, w1 + tid * 8);
        cp_async16(o + 8192, w2 + r * 192 + 64 + c * 8);
        cp_async16(sbase + PS_W2 + r * 272 + c * 16, w2 + r * 192 + c * 8);
        cp_async16(sbase + PS_W2 + r * 272 + 128 + c * 16, w2 + r * 192 + 128 + c * 8);
        if (tid < 384) cp_async16(sbase + PS_WR + (tid / 24) * 400 + (tid % 24) * 16, wrbf + tid * 8);
    }
    {
        int2* ps = reinterpret_cast<int2*>(smem + PS_SRC);
        int2* pd = reinterpret_cast<int2*>(smem + PS_DST);
        int2* pk = reinterpret_cast<int2*>(smem + PS_KEY);
#pragma unroll 1
        for (int i = tid; i < npair; i += M_THREADS) {
            asm volatile("cp.async.commit_group;\ncp.async.wait_group 5;" ::: "memory");
            const int2 es = ps[i], ed = pd[i];
            int rx[2], ry[2], key[2];
#pragma unroll
            for (int b = 0; b < 2; b++) {
                const uint32_t sn = b ? es.y : es.x, dn = b ? ed.y : ed.x;
                const uint32_t as = sbase + PS_POS + sn * 6, ad = sbase + PS_POS + dn * 6;
                uint32_t sa, sb, da, db;
                asm volatile("ld.shared.u32 %0, [%2];\nld.shared.u32 %1, [%2+4];" : "=r"(sa), "=r"(sb) : "r"(as & ~3u));
                asm volatile("ld.shared.u32 %0, [%2];\nld.shared.u32 %1, [%2+4];" : "=r"(da), "=r"(db) : "r"(ad & ~3u));
                const uint32_t rxy = hsub2(__funnelshift_r(sa, sb, as << 3), __funnelshift_r(da, db, ad << 3));
                const uint32_t rz = hsub2(__funnelshift_r(sb, 0u, as << 3), __funnelshift_r(db, 0u, ad << 3));
                const uint32_t qxy = hmul2(rxy, rxy), qz = hmul2(rz, rz);
                const float sum = (__uint_as_float(qxy << 16) + __uint_as_float(qxy & 0xffff0000u)) + __uint_as_float(qz << 16);
                const uint32_t c = dn / NPC, dl = dn - c * NPC;
                rx[b] = hmul2(rxy, 0x1e801e80u) | ((dl * 0x08002000u) & 0x60006000u);
                ry[b] = __byte_perm(hmul2(rz, 0x1e801e80u), sn, 0x5410) | ((dl * 0x02000200u) & 0x80006000u);
                const uint32_t ba = sbase + PS_HIST + (c * NQ + (dl >> 3)) * 4;
                asm volatile("{\n.reg .pred p;\nsetp.lt.f32 p, %2, 0f41BF8000;\nmov.u32 %0, 0x80000000;\n"
                             "@p atom.shared.add.u32 %0, [%1], 1;\n}\n" : "=r"(key[b]) : "r"(ba), "f"(sum) : "memory");
                key[b] |= ba << 13;
            }
            ps[i] = make_int2(rx[0], rx[1]);
            pd[i] = make_int2(ry[0], ry[1]);
            pk[i] = make_int2(key[0], key[1]);
        }
        STAMP(18, 0);
        asm volatile("cp.async.wait_all;" ::: "memory");
        asm volatile("fence.proxy.async.shared::cta;" ::: "memory");
        __syncthreads();
        STAMP(2, 0);
        if (is_prod) {
            const int pt = tid - UNITS * 128;
            scan1536(hist, pt);
            STAMP(16, 384);
#pragma unroll 1
            for (int gi = cta * 256 + pt; gi < min(cta * 256 + 256, NTAB * NRBF); gi += 128) {
                const float d = __uint_as_float((uint32_t)(DBASE + (gi >> 4)) << 16);
                const float arg = bf16r(d * __uint_as_float((uint32_t)freq_bits << 16));
                float sn;
                if (fabsf(arg) < 1000.f) {
                    const float k = rintf(arg * 0.15915494309189535f);
                    sn = __sinf(fmaf(k, 1.7484556000744883e-7f, fmaf(k, -6.2831854820251465f, arg)));
                } else {
                    sn = sinf(arg);
                }
                const float rbf = bf16r(__fdividef(bf16r(sn), d));
                const float ca = bf16r(bf16r(3.14159265358979f * d) * 0.2f);
                const float fc = 0.5f * bf16r(bf16r(__cosf(ca)) + 1.0f);
                g_G[gi] = __float2bfloat16_rn(rbf * fc);
            }
            if (pt < 2) mbar_init(ghbar + 8 + pt * 8, 128);
            STAMP(17, 384);
        } else {
            const uint32_t tb = sbase + (warp >> 2) * STAGE_BYTES;
            const uint32_t fo = ((lane & 7) + 8 * (lane >> 4)) * 128 + ((uint32_t)((2 * (warp & 3) + ((lane >> 3) & 1)) ^ (lane & 7)) << 4);
            const uint32_t dh = (tb >> 4) | (1u << 16);
            uint32_t x[2][4];
#pragma unroll 1
            for (int it = 0; it < 2; it++) {
                uint32_t a[4][4];
                float d[16];
#pragma unroll
                for (int q = 0; q < 4; q++) ldsm4t(a[q], sbase + PS_W1 + it * 8192 + q * 2048 + fo);
                asm volatile("wgmma.fence.sync.aligned;" ::: "memory");
                wgmma_n32<0, DESC_H>(d, a[0], dh);
                wgmma_n32<1, DESC_H>(d, a[1], dh + 2);
                wgmma_n32<1, DESC_H>(d, a[2], dh + 4);
                wgmma_n32<1, DESC_H>(d, a[3], dh + 6);
                asm volatile("wgmma.commit_group.sync.aligned;" ::: "memory");
                asm volatile("wgmma.wait_group.sync.aligned 0;" ::: "memory");
                reg_fence16(d);
#pragma unroll
                for (int i = 0; i < 8; i++) x[i >> 2][i & 3] = pack_bf16(d[2 * i], d[2 * i + 1]);
                if (it) break;
                asm volatile("bar.sync %0, 128;" ::"r"(1 + (warp >> 2)) : "memory");
#pragma unroll 1
                for (int s = 0; s < 2; s++) {
                    uint32_t y[4];
#pragma unroll
                    for (int e = 0; e < 4; e++) {
                        const float z0 = __uint_as_float(x[0][e] << 16), z1 = __uint_as_float(x[0][e] & 0xffff0000u);
                        float e0, e1;
                        asm("ex2.approx.ftz.f32 %0, %1;" : "=f"(e0) : "f"(z0 * -1.4426950408889634f));
                        asm("ex2.approx.ftz.f32 %0, %1;" : "=f"(e1) : "f"(z1 * -1.4426950408889634f));
                        asm("rcp.approx.ftz.f32 %0, %1;" : "=f"(e0) : "f"(e0 + 1.0f));
                        asm("rcp.approx.ftz.f32 %0, %1;" : "=f"(e1) : "f"(e1 + 1.0f));
                        y[e] = pack_bf16(z0 * e0, z1 * e1);
                        x[0][e] = x[1][e];
                    }
                    stsm4t(tb + fo + s * 2048, y);
                }
                asm volatile("fence.proxy.async.shared::cta;" ::: "memory");
                asm volatile("bar.sync %0, 128;" ::"r"(1 + (warp >> 2)) : "memory");
                STAMP(14, 0);
            }
#pragma unroll 1
            for (int j = 1; j < 4; j++) {
                uint32_t v[2][4];
                ldsm4t(v[0], tb + fo + j * 4096);
                ldsm4t(v[1], tb + fo + j * 4096 + 2048);
#pragma unroll
                for (int e = 0; e < 8; e++) v[e >> 2][e & 3] = hmul2(v[e >> 2][e & 3], x[e >> 2][e & 3]);
                stsm4t(tb + fo + j * 4096, v[0]);
                stsm4t(tb + fo + j * 4096 + 2048, v[1]);
            }
            STAMP(15, 0);
        }
        __syncthreads();
        STAMP(3, 0);
#pragma unroll 2
        for (int node = warp; node < nnodes; node += 16) {
            const int row = node & 31;
            reinterpret_cast<uint4*>(g_tab + (size_t)(cta * NPC + node) * ROWB)[lane] = *reinterpret_cast<const uint4*>(
                smem + (node >> 5) * STAGE_BYTES + (lane >> 3) * 4096 + row * 128 + (((lane ^ row) & 7) << 4));
        }
        STAMP(8, 0);
#pragma unroll 1
        for (int i = tid; i < npair; i += M_THREADS) {
            const int2 k = pk[i], x = ps[i], y = pd[i];
            int o0, o1;
            asm volatile("ld.shared.u32 %0, [%1];" : "=r"(o0) : "r"((k.x >> 13) & 0x3ffff));
            asm volatile("ld.shared.u32 %0, [%1];" : "=r"(o1) : "r"((k.y >> 13) & 0x3ffff));
            int2* sorted = reinterpret_cast<int2*>(smem + PS_POS);
            if (k.x >= 0) sorted[o0 + (k.x & 8191)] = make_int2(x.x, y.x);
            if (k.y >= 0) sorted[o1 + (k.y & 8191)] = make_int2(x.y, y.y);
        }
        __syncthreads();
        STAMP(4, 0);
        const int n16 = (hist[NBIN] + 1) >> 1;
#pragma unroll 1
        for (int i = tid; i < n16; i += M_THREADS)
            reinterpret_cast<uint4*>(g_rec + cta * CH)[i] = reinterpret_cast<const uint4*>(smem + PS_POS)[i];
        __syncthreads();
        STAMP(5, 0);
    }
    const int g = lane >> 2, t = lane & 3;
    unsigned short* pf = reinterpret_cast<unsigned short*>(smem + PS_PF);
    {
        const uint32_t tag = ((epoch / NCTA + 1) & 0xffffu) << 16;
        if (warp < 9) {
            const int c = min(tid >> 1, NCTA - 1);
            const int* h = hist + c * NQ + (tid & 1) * 7;
            uint4 v = make_uint4(h[0] | (h[1] << 16), h[2] | (h[3] << 16), h[4] | (h[5] << 16), h[6] | tag);
            __threadfence();
            asm volatile("st.relaxed.gpu.global.v4.u32 [%0], {%1,%2,%3,%4};" ::"l"(g_pfx + (cta * NCTA + c) * 2 + (tid & 1)),
                         "r"(v.x), "r"(v.y), "r"(v.z), "r"(v.w) : "memory");
        } else if (warp == 15) {
            if (lane < 2 * UNITS * STAGES) mbar_init(sbase + (lane >> 1) * STAGE_BYTES + ST_CTL + (lane & 1) * 8, (lane & 1) ? 4 : 64);
            if (lane == 31) atomicInc(&g_cnt, NCTA * 65536u - 1);
        }
        STAMP(6, 0);
        const int p = min(warp + 16 * (lane >> 1), NCTA - 1);
        uint4 v;
        int spin = 0;
        do {
            asm volatile("ld.acquire.gpu.global.v4.u32 {%0,%1,%2,%3}, [%4];" : "=r"(v.x), "=r"(v.y), "=r"(v.z), "=r"(v.w)
                         : "l"(g_pfx + (p * NCTA + cta) * 2 + (lane & 1)) : "memory");
        } while (__any_sync(0xffffffffu, (v.w ^ tag) & 0xffff0000u) && ++spin < (1 << 22));
        STAMP(7, 0);
        reinterpret_cast<uint4*>(pf)[p * 2 + (lane & 1)] = v;
#pragma unroll 1
        for (int k = 0, pp = warp; pp < NCTA; k += 2, pp += 16) {
            const int i = (__shfl_sync(0xffffffffu, v.x, k) & 0xfffe) + 2 * lane;
            const int e = __shfl_sync(0xffffffffu, v.y, k + 1) >> 16;
            if (i < e) cp_async16(sbase + (3 + (pp >> 5)) * STAGE_BYTES + (pp & 31) * 512 + lane * 16, g_rec + pp * CH + i);
        }
        __syncwarp();
#pragma unroll 1
        for (int e = lane; e < 96; e += 32) {
            const int k = e / NQ, q = e - k * NQ, pp = warp + 16 * k;
            if (pp < NCTA) b2[q * NCTA + pp] = pf[pp * 16 + q + 1 + (q >= 6)] - pf[pp * 16 + q + (q >= 7)];
        }
        __syncthreads();
        STAMP(9, 0);
        if (is_prod) {
            scan1536(b2, tid - UNITS * 128);
        } else {
#pragma unroll 1
            for (int i = tid; i < (NTAB - HOT0) * 2; i += UNITS * 128) cp_async16(sbase + MS_GH + i * 16, g_G + HOT0 * NRBF + i * 8);
        }
        asm volatile("cp.async.wait_all;" ::: "memory");
    }
    __syncthreads();
    STAMP(11, 0);
    if (b2[NBIN] <= RCAP) {
        uint2* srec = reinterpret_cast<uint2*>(smem + MS_REC);
#pragma unroll 1
        for (int p = 2 * warp + (lane >> 4); p < NCTA; p += 32) {
            const int beg = pf[p * 16], end = pf[p * 16 + NQ + 1];
            const uint4* raw = reinterpret_cast<const uint4*>(smem + (3 + (p >> 5)) * STAGE_BYTES + (p & 31) * 512);
#pragma unroll 1
            for (int o = lane & 15, i = (beg & ~1) + 2 * o; i < end; o += 16, i += 32) {
                const uint4 v = o < 32 ? raw[o] : __ldcg(reinterpret_cast<const uint4*>(g_rec + p * CH + i));
                const int q0 = (int)(((v.x >> 30) & 1u) | ((v.y >> 12) & 6u) | ((v.y >> 28) & 8u));
                const int q1 = (int)(((v.z >> 30) & 1u) | ((v.w >> 12) & 6u) | ((v.w >> 28) & 8u));
                if (i >= beg) srec[b2[q0 * NCTA + p] - pf[p * 16 + q0 + (q0 >= 7)] + i] = make_uint2(v.x, v.y);
                if (i + 1 < end) srec[b2[q1 * NCTA + p] - pf[p * 16 + q1 + (q1 >= 7)] + i + 1] = make_uint2(v.z, v.w);
            }
        }
    }
    __syncthreads();
    STAMP(12, 0);

    if (is_prod) {
        asm volatile("setmaxnreg.dec.sync.aligned.u32 80;");
        const int unit = warp - UNITS * 4;
        if (unit < UNITS) {
            asm volatile("bar.sync 6, 480;" ::: "memory");
            STAMP(21, 384);
            if (__reduce_or_sync(0xffffffffu, (uint32_t)b2[NBIN]) <= RCAP) producer_loop<true>(smem, sv, N, unit);
            else producer_loop<false>(smem, sv, N, unit);
            GSTAMP(22 + unit, 384 + 32 * unit);
        }
    } else {
        asm volatile("setmaxnreg.inc.sync.aligned.u32 144;");
        const int unit = warp >> 2, w = warp & 3;
        const uint32_t ubase = sbase + unit * STAGES * STAGE_BYTES;
        uint32_t wa[3][4], pa[2][4][4];
        {
            const int krow = (lane & 7) + 8 * (lane >> 4), mcol = 2 * w + ((lane >> 3) & 1);
#pragma unroll
            for (int q = 0; q < 4; q++) {
                ldsm4t(pa[0][q], sbase + PS_W2 + (16 * q + krow) * 272 + mcol * 16);
                ldsm4t(pa[1][q], sbase + PS_W2 + (16 * q + krow) * 272 + 128 + mcol * 16);
            }
#pragma unroll
            for (int p = 0; p < 3; p++) ldsm4t(wa[p], sbase + PS_WR + krow * 400 + p * 128 + mcol * 16);
            asm volatile("bar.arrive 6, 480;" ::: "memory");
        }
        float acc[4][4];
#pragma unroll
        for (int c = 0; c < 4; c++)
#pragma unroll
            for (int e = 0; e < 4; e++) acc[c][e] = 0.f;
        const int erow = (lane & 7) + 8 * (lane >> 4);
        const int ehalf = (lane >> 3) & 1;
        const uint32_t ua = pin(4096 + erow * 128 + ((uint32_t)((2 * w + ehalf) ^ (lane & 7)) << 4));
        const uint32_t ra = pin(ST_R + t * 16);
        const uint32_t ub = __reduce_or_sync(0xffffffffu, ubase);
        uint32_t sb = ub;
        uint32_t ph = 0;
        while (true) {
            mbar_wait(sb + ST_CTL, ph);
            {
                const uint32_t dh = (sb >> 4) | (1u << 16);
                const uint32_t dg = dh + (ST_G >> 4);
                uint32_t m[2][4], wv[2][4], u[3][4], rr[3][2];
                float p0[16], f0[16], fv[16];
                asm volatile("wgmma.fence.sync.aligned;" ::: "memory");
                wgmma_n32<0, DESC_G>(f0, wa[2], dg);
                wgmma_n32<0, DESC_H>(p0, pa[1][0], dh);
                wgmma_n32<1, DESC_H>(p0, pa[1][1], dh + 2);
                wgmma_n32<1, DESC_H>(p0, pa[1][2], dh + 4);
                wgmma_n32<1, DESC_H>(p0, pa[1][3], dh + 6);
                wgmma_n32<0, DESC_G>(fv, wa[1], dg);
                asm volatile("wgmma.commit_group.sync.aligned;" ::: "memory");
                asm volatile("wgmma.wait_group.sync.aligned 1;" ::: "memory");
#pragma unroll
                for (int j = 0; j < 3; j++) {
                    ldsm4t(u[j], sb + ua + j * 4096);
                    asm volatile("ld.shared.v2.u32 {%0,%1}, [%2];" : "=r"(rr[j][0]), "=r"(rr[j][1]) : "r"(sb + ra + j * 64));
                }
                asm volatile("wgmma.wait_group.sync.aligned 0;" ::: "memory");
                reg_fence16(fv); reg_fence16(f0); reg_fence16(p0);
#pragma unroll
                for (int i = 0; i < 8; i++) {
                    m[i >> 2][i & 3] = pack_bf16(f0[2 * i] * p0[2 * i], f0[2 * i + 1] * p0[2 * i + 1]);
                    wv[i >> 2][i & 3] = pack_bf16(fv[2 * i], fv[2 * i + 1]);
                }
                asm volatile("wgmma.fence.sync.aligned;" ::: "memory");
                wgmma_n32<0, DESC_G>(f0, wa[0], dg);
                wgmma_n32<0, DESC_H>(p0, pa[0][0], dh);
                wgmma_n32<1, DESC_H>(p0, pa[0][1], dh + 2);
                wgmma_n32<1, DESC_H>(p0, pa[0][2], dh + 4);
                wgmma_n32<1, DESC_H>(p0, pa[0][3], dh + 6);
                asm volatile("wgmma.commit_group.sync.aligned;" ::: "memory");
                asm volatile("wgmma.wait_group.sync.aligned 1;" ::: "memory");
                uint32_t v1[3][4], r1[3][2];
#pragma unroll
                for (int j = 0; j < 3; j++) {
                    ldsm4t(v1[j], sb + ua + j * 4096 + 2048);
                    asm volatile("ld.shared.v2.u32 {%0,%1}, [%2];" : "=r"(r1[j][0]), "=r"(r1[j][1]) : "r"(sb + ra + j * 64 + 8));
                }
#pragma unroll
                for (int j = 0; j < 3; j++)
#pragma unroll
                    for (int e = 0; e < 4; e++) u[j][e] = hfma2(m[0][e], rr[j][e >> 1], hmul2(u[j][e], wv[0][e]));
#pragma unroll
                for (int j = 0; j < 3; j++)
#pragma unroll
                    for (int e = 0; e < 4; e++) v1[j][e] = hfma2(m[1][e], r1[j][e >> 1], hmul2(v1[j][e], wv[1][e]));
#pragma unroll
                for (int j = 0; j < 3; j++)
                    asm volatile("{\n.reg .pred p;\nsetp.lt.s32 p, %5, 0;\n@p st.shared.v4.u32 [%0], {%1,%2,%3,%4};\n}\n"
                                 ::"r"(ra), "r"(v1[j][0]), "r"(v1[j][1]), "r"(v1[j][2]), "r"(v1[j][3]), "r"(N) : "memory");
                asm volatile("wgmma.wait_group.sync.aligned 0;" ::: "memory");
                reg_fence16(f0); reg_fence16(p0);
                uint32_t sf[4];
                ldsm4t(sf, sb + ST_S + (lane << 4));
#pragma unroll
                for (int i = 0; i < 8; i++)
                    m[i >> 2][i & 3] = pack_bf16(f0[2 * i] * p0[2 * i], f0[2 * i + 1] * p0[2 * i + 1]);
#pragma unroll
                for (int j = 0; j < 3; j++) mma16816(acc[j + 1], u[j], sf[0], sf[1]);
                mma16816(acc[0], m[0], sf[0], sf[1]);
#pragma unroll
                for (int j = 0; j < 3; j++) mma16816(acc[j + 1], v1[j], sf[2], sf[3]);
                mma16816(acc[0], m[1], sf[2], sf[3]);
            }
            uint32_t flags;
            asm volatile("ld.shared.u32 %0, [%1+16];" : "=r"(flags) : "r"(sb + ST_CTL));
            if (flags) {
                if (flags & 8u) break;
                float* part = reinterpret_cast<float*>(smem + MS_PART) + (tid & 127);
                if (flags & 4u) {
#pragma unroll
                    for (int i = 0; i < 16; i++) part[(unit - 1) * 2048 + i * 128] = acc[i >> 2][i & 3];
                    mbar_arrive(sbase + MS_BAR + unit * 8);
                } else {
#pragma unroll 1
                    for (int k = 0; k < 2; k++) {
                        if (flags & (16u << k)) {
                            mbar_wait(sbase + MS_BAR + 8 + k * 8, 0);
#pragma unroll
                            for (int i = 0; i < 16; i++) acc[i >> 2][i & 3] += part[k * 2048 + i * 128];
                        }
                    }
                    const uint32_t ea = sb + (lane >> 4) * 4096 + (24 + (lane & 7)) * 128 +
                                        ((uint32_t)((2 * w + ((lane >> 3) & 1)) ^ (lane & 7)) << 4);
#pragma unroll
                    for (int k = 0; k < 2; k++) {
                        uint32_t v[4];
                        ldsm4t(v, ea + k * 8192);
#pragma unroll
                        for (int e = 0; e < 4; e++)
                            v[e] = pack_bf16(__uint_as_float(v[e] << 16) + acc[2 * k + (e >> 1)][2 * (e & 1)],
                                             __uint_as_float(v[e] & 0xffff0000u) + acc[2 * k + (e >> 1)][2 * (e & 1) + 1]);
                        stsm4t(ea + k * 8192, v);
                    }
                    __syncwarp();
                    const int ln0 = (int)(flags >> 8) * GRP + (lane >> 2);
                    const int c0 = (lane >> 1) & 1, ch = 2 * w + (lane & 1);
                    uint4* op = reinterpret_cast<uint4*>(out + (size_t)(blockIdx.x * NPC + ln0) * 256) + c0 * 8 + ch;
                    const uint32_t ia = sb + c0 * 4096 + (24 + (lane >> 2)) * 128 + ((uint32_t)(ch ^ (lane >> 2)) << 4);
#pragma unroll
                    for (int k = 0; k < 2; k++) {
                        asm volatile("{\n.reg .pred p;\n.reg .b32 a, b, c, d;\nsetp.lt.s32 p, %2, %3;\n"
                                     "ld.shared.v4.u32 {a, b, c, d}, [%0];\n"
                                     "@p st.global.v4.u32 [%1], {a, b, c, d};\n}\n"
                                     ::"r"(ia + k * 8192), "l"(op + k * 16), "r"(ln0), "r"(min(NPC, N - (int)blockIdx.x * NPC)) : "memory");
                    }
                }
#pragma unroll
                for (int i = 0; i < 16; i++) acc[i >> 2][i & 3] = 0.f;
            }
            asm volatile("{\n.reg .pred p;\nelect.sync _|p, 0xffffffff;\n@p mbarrier.arrive.shared::cta.b64 _, [%0];\n}\n"
                         ::"r"(sb + ST_CTL + 8) : "memory");
            sb += STAGE_BYTES;
            if (sb == ub + STAGES * STAGE_BYTES) { sb = ub; ph ^= 1; }
        }
        GSTAMP(26 + unit, 128 * unit);
    }
}

}

extern "C" void kernel_launch(void* const* d_in, const int* in_sizes, int n_in, void* d_out, int out_size) {
    const __nv_bfloat16* sv = (const __nv_bfloat16*)d_in[0];
    const __nv_bfloat16* pos = (const __nv_bfloat16*)d_in[1];
    const int* src = (const int*)d_in[2];
    const int* dst = (const int*)d_in[3];
    const __nv_bfloat16* freqs = (const __nv_bfloat16*)d_in[4];
    const __nv_bfloat16* w1 = (const __nv_bfloat16*)d_in[5];
    const __nv_bfloat16* w2 = (const __nv_bfloat16*)d_in[6];
    const __nv_bfloat16* wrbf = (const __nv_bfloat16*)d_in[7];
    __nv_bfloat16* out = (__nv_bfloat16*)d_out;
    const int N = in_sizes[1] / 3;
    const int E = in_sizes[2];

    static bool init = false;
    if (!init) {
        cudaFuncSetAttribute(fused_kernel, cudaFuncAttributeMaxDynamicSharedMemorySize, M_SMEM);
        init = true;
    }
    fused_kernel<<<NCTA, M_THREADS, M_SMEM, cudaStreamPerThread>>>(sv, pos, src, dst, freqs, w1, w2, wrbf, out, N, E);
}
```

```cpp
#include <cuda_runtime.h>
#include <cuda_bf16.h>
#include <stdint.h>

namespace {

constexpr int D = 64;
constexpr int NRBF = 16;
constexpr int MAXN = 10000;
constexpr int MAXE = 640000;
constexpr int NCTA = 132;
constexpr int GRP = 8;
constexpr int NPC = (MAXN + NCTA - 1) / NCTA;
constexpr int NQ = (NPC + GRP - 1) / GRP;
constexpr int NBIN = NCTA * NQ;
constexpr int CH = 4864;
constexpr int DBASE = 0x38C0;
constexpr int DEND = 0x40A0;
constexpr int NTAB = DEND - DBASE;
constexpr int ROWB = 512;

__device__ __align__(128) unsigned char g_tab[(size_t)(MAXN + 16) * ROWB];
__device__ __align__(128) __nv_bfloat16 g_G[NTAB * NRBF];
__device__ __align__(128) uint2 g_rec[NCTA * CH];
__device__ __align__(128) uint4 g_pfx[NCTA * NCTA * 2];
__device__ unsigned int g_cnt;

#define STAMP(k, tt) do {} while (0)
#define GSTAMP(k, tt) do {} while (0)

__device__ __forceinline__ uint32_t smem_u32(const void* p) { return (uint32_t)__cvta_generic_to_shared(p); }
__device__ __forceinline__ uint32_t pack_bf16(float lo, float hi) {
    uint32_t r;
    asm("cvt.rn.bf16x2.f32 %0, %1, %2;" : "=r"(r) : "f"(hi), "f"(lo));
    return r;
}
__device__ __forceinline__ float bf16r(float x) { return __uint_as_float(pack_bf16(0.f, x) & 0xffff0000u); }
__device__ __forceinline__ uint32_t hmul2(uint32_t a, uint32_t b) {
    uint32_t r;
    asm("mul.rn.bf16x2 %0, %1, %2;" : "=r"(r) : "r"(a), "r"(b));
    return r;
}
__device__ __forceinline__ uint32_t hsub2(uint32_t a, uint32_t b) {
    uint32_t r;
    asm("sub.rn.bf16x2 %0, %1, %2;" : "=r"(r) : "r"(a), "r"(b));
    return r;
}
__device__ __forceinline__ uint32_t hfma2(uint32_t a, uint32_t b, uint32_t c) {
    uint32_t r;
    asm("fma.rn.bf16x2 %0, %1, %2, %3;" : "=r"(r) : "r"(a), "r"(b), "r"(c));
    return r;
}
__device__ __forceinline__ void mma16816(float (&c)[4], const uint32_t (&a)[4], uint32_t b0, uint32_t b1) {
    asm volatile("mma.sync.aligned.m16n8k16.row.col.f32.bf16.bf16.f32 {%0,%1,%2,%3}, {%4,%5,%6,%7}, {%8,%9}, {%0,%1,%2,%3};"
                 : "+f"(c[0]), "+f"(c[1]), "+f"(c[2]), "+f"(c[3])
                 : "r"(a[0]), "r"(a[1]), "r"(a[2]), "r"(a[3]), "r"(b0), "r"(b1));
}
__device__ __forceinline__ void mma16816_z(float (&c)[4], const uint32_t (&a)[4], uint32_t b0, uint32_t b1) {
    asm volatile("mma.sync.aligned.m16n8k16.row.col.f32.bf16.bf16.f32 {%0,%1,%2,%3}, {%4,%5,%6,%7}, {%8,%9}, {%10,%10,%10,%10};"
                 : "=f"(c[0]), "=f"(c[1]), "=f"(c[2]), "=f"(c[3])
                 : "r"(a[0]), "r"(a[1]), "r"(a[2]), "r"(a[3]), "r"(b0), "r"(b1), "f"(0.f));
}
__device__ __forceinline__ void ldsm4(uint32_t (&r)[4], uint32_t addr) {
    asm volatile("ldmatrix.sync.aligned.m8n8.x4.shared.b16 {%0,%1,%2,%3}, [%4];"
                 : "=r"(r[0]), "=r"(r[1]), "=r"(r[2]), "=r"(r[3]) : "r"(addr));
}
__device__ __forceinline__ void ldsm4t(uint32_t (&r)[4], uint32_t addr) {
    asm volatile("ldmatrix.sync.aligned.m8n8.x4.trans.shared.b16 {%0,%1,%2,%3}, [%4];"
                 : "=r"(r[0]), "=r"(r[1]), "=r"(r[2]), "=r"(r[3]) : "r"(addr));
}
__device__ __forceinline__ void stsm4t(uint32_t addr, const uint32_t (&r)[4]) {
    asm volatile("stmatrix.sync.aligned.m8n8.x4.trans.shared.b16 [%0], {%1,%2,%3,%4};"
                 ::"r"(addr), "r"(r[0]), "r"(r[1]), "r"(r[2]), "r"(r[3]) : "memory");
}
__device__ __forceinline__ void cp_async16(uint32_t dst, const void* src) {
    asm volatile("cp.async.cg.shared.global [%0], [%1], 16;" ::"r"(dst), "l"(src) : "memory");
}
__device__ __forceinline__ void mbar_init(uint32_t bar, int cnt) {
    asm volatile("mbarrier.init.shared::cta.b64 [%0], %1;" ::"r"(bar), "r"(cnt) : "memory");
}
__device__ __forceinline__ void mbar_arrive(uint32_t bar) {
    asm volatile("mbarrier.arrive.shared::cta.b64 _, [%0];" ::"r"(bar) : "memory");
}
__device__ __forceinline__ void mbar_expect_tx(uint32_t bar, uint32_t bytes) {
    asm volatile("mbarrier.arrive.expect_tx.shared::cta.b64 _, [%0], %1;" ::"r"(bar), "r"(bytes) : "memory");
}
__device__ __forceinline__ void mbar_wait(uint32_t bar, uint32_t parity) {
    asm volatile(
        "{\n.reg .pred p;\n.reg .u32 n;\nmov.u32 n, 0;\n"
        "WAIT_%=:\n"
        "mbarrier.try_wait.parity.shared::cta.b64 p, [%0], %1, %2;\n"
        "@p bra DONE_%=;\n"
        "add.u32 n, n, 1;\n"
        "setp.lt.u32 p, n, 100000;\n"
        "@p bra WAIT_%=;\n"
        "exit;\n"
        "DONE_%=:\n}\n" ::"r"(bar), "r"(parity), "r"(10000u) : "memory");
}
__device__ __forceinline__ void bulk_g2s(uint32_t dst, const void* src, uint32_t bytes, uint32_t bar) {
    asm volatile("cp.async.bulk.shared::cluster.global.mbarrier::complete_tx::bytes [%0], [%1], %2, [%3];"
                 ::"r"(dst), "l"(src), "r"(bytes), "r"(bar) : "memory");
}
__device__ __forceinline__ void bulk_s2g(void* dst, uint32_t src, uint32_t bytes) {
    asm volatile("cp.async.bulk.global.shared::cta.bulk_group [%0], [%1], %2;" ::"l"(dst), "r"(src), "r"(bytes) : "memory");
}

constexpr int UNITS = 2;
constexpr int STAGES = 4;
constexpr int M_THREADS = 512;
constexpr int ST_G = 4 * 4096;
constexpr int ST_S = ST_G + 1024;
constexpr int ST_R = ST_S + 512;
constexpr int ST_CTL = ST_R + 192;
constexpr int STAGE_BYTES = ST_S + 1024;
constexpr int RCAP = 4800;
constexpr int HOT0 = 0x3F00 - DBASE;
constexpr int MS_REC = 9 * STAGE_BYTES;
constexpr int MS_PART = MS_REC + RCAP * 8;
constexpr int MS_GH = MS_PART + 8192;
constexpr int MS_B2 = MS_GH + (NTAB - HOT0) * 32;
constexpr int MS_MISC = MS_B2 + 1536 * 4;
constexpr int MS_BAR = MS_MISC + 32 * 4;
constexpr int MS_DBG = MS_BAR + 64;
constexpr int M_SMEM = MS_DBG + 256;
constexpr int EPC = 4852;
constexpr int PS_POS = 3 * STAGE_BYTES;
constexpr int PS_W1 = PS_POS + 60032;
constexpr int PS_WR = 7 * STAGE_BYTES + 4096;
constexpr int PS_HIST = PS_WR + 16 * 400;
constexpr int PS_W2 = 8 * STAGE_BYTES;
constexpr int PS_SRC = MS_REC;
constexpr int PS_DST = PS_SRC + CH * 4;
constexpr int PS_KEY = PS_DST + CH * 4;
constexpr int PS_PF = MS_PART;
static_assert(PS_W1 % 128 == 0 && PS_W1 + 16384 <= PS_WR && PS_HIST + (1536 + 32) * 4 <= 7 * STAGE_BYTES + ST_CTL &&
              64 * 272 <= ST_CTL && PS_KEY + CH * 4 <= MS_B2 && EPC * NCTA >= MAXE && EPC <= CH && CH * 8 <= 60032,
              "phase-1 layout");
static_assert(M_SMEM <= 232448, "smem");
static_assert(MS_BAR % 8 == 0 && MS_GH % 16 == 0 && STAGE_BYTES % 1024 == 0, "align");

template <int ACC, uint32_t HI>
__device__ __forceinline__ void wgmma_n32(float (&d)[16], const uint32_t (&a)[4], uint32_t lo) {
    if (ACC) {
        asm volatile("{\n.reg .b64 dd;\nmov.b64 dd, {%20, %21};\n"
                     "wgmma.mma_async.sync.aligned.m64n32k16.f32.bf16.bf16 {%0,%1,%2,%3,%4,%5,%6,%7,%8,%9,%10,%11,%12,%13,%14,%15}, {%16,%17,%18,%19}, dd, 1, 1, 1, 0;\n}\n"
                     : "+f"(d[0]), "+f"(d[1]), "+f"(d[2]), "+f"(d[3]), "+f"(d[4]), "+f"(d[5]), "+f"(d[6]), "+f"(d[7]),
                       "+f"(d[8]), "+f"(d[9]), "+f"(d[10]), "+f"(d[11]), "+f"(d[12]), "+f"(d[13]), "+f"(d[14]), "+f"(d[15])
                     : "r"(a[0]), "r"(a[1]), "r"(a[2]), "r"(a[3]), "r"(lo), "n"(HI));
    } else {
        asm volatile("{\n.reg .b64 dd;\nmov.b64 dd, {%20, %21};\n"
                     "wgmma.mma_async.sync.aligned.m64n32k16.f32.bf16.bf16 {%0,%1,%2,%3,%4,%5,%6,%7,%8,%9,%10,%11,%12,%13,%14,%15}, {%16,%17,%18,%19}, dd, 0, 1, 1, 0;\n}\n"
                     : "=f"(d[0]), "=f"(d[1]), "=f"(d[2]), "=f"(d[3]), "=f"(d[4]), "=f"(d[5]), "=f"(d[6]), "=f"(d[7]),
                       "=f"(d[8]), "=f"(d[9]), "=f"(d[10]), "=f"(d[11]), "=f"(d[12]), "=f"(d[13]), "=f"(d[14]), "=f"(d[15])
                     : "r"(a[0]), "r"(a[1]), "r"(a[2]), "r"(a[3]), "r"(lo), "n"(HI));
    }
}
constexpr uint32_t DESC_H = 64u | (1u << 30);
constexpr uint32_t DESC_G = 16u | (3u << 30);
__device__ __forceinline__ void reg_fence16(float (&d)[16]) {
    asm volatile("" : "+f"(d[0]), "+f"(d[1]), "+f"(d[2]), "+f"(d[3]), "+f"(d[4]), "+f"(d[5]), "+f"(d[6]), "+f"(d[7]),
                      "+f"(d[8]), "+f"(d[9]), "+f"(d[10]), "+f"(d[11]), "+f"(d[12]), "+f"(d[13]), "+f"(d[14]), "+f"(d[15]) :: "memory");
}
__device__ __forceinline__ uint32_t pin(uint32_t x) { return __shfl_sync(0xffffffffu, x, threadIdx.x & 31); }

__device__ __forceinline__ void scan1536(int* h, int pt) {
    int4* h4 = reinterpret_cast<int4*>(h) + pt * 3;
    int4 a = h4[0], b = h4[1], c = h4[2];
    a.y += a.x; a.z += a.y; a.w += a.z; b.x += a.w; b.y += b.x; b.z += b.y; b.w += b.z;
    c.x += b.w; c.y += c.x; c.z += c.y; c.w += c.z;
    int incl = c.w;
#pragma unroll
    for (int o = 1; o < 32; o <<= 1) {
        const int v = __shfl_up_sync(0xffffffffu, incl, o);
        if ((pt & 31) >= o) incl += v;
    }
    if ((pt & 31) == 31) h[1536 + (pt >> 5)] = incl;
    asm volatile("bar.sync 4, 128;" ::: "memory");
    const int ex = __reduce_add_sync(0xffffffffu, (pt & 31) < (pt >> 5) ? h[1536 + (pt & 31)] : 0) + incl - c.w;
    h4[0] = make_int4(ex, ex + a.x, ex + a.y, ex + a.z);
    h4[1] = make_int4(ex + a.w, ex + b.x, ex + b.y, ex + b.z);
    h4[2] = make_int4(ex + b.w, ex + c.x, ex + c.y, ex + c.z);
}

template <bool FITS>
__device__ __forceinline__ void producer_loop(unsigned char* smem, const __nv_bfloat16* __restrict__ sv, int N, int pw) {
    const uint32_t sbase = smem_u32(smem);
    const int un = pw & 1;
    const uint32_t ubase = sbase + un * STAGES * STAGE_BYTES;
    const int* b2 = reinterpret_cast<const int*>(smem + MS_B2);
    const int ln = pin(threadIdx.x & 31);
    const int r4 = ln >> 3;
    const unsigned char* gsrc = g_tab + (ln & 7) * 16;
    asm volatile("" : "+l"(gsrc));
    const uint32_t d0 = r4 * 128 + (((ln & 7) ^ r4) << 4);
    const uint32_t goff = ST_G + ln * 32 + (((ln >> 2) & 1) << 4);
    const uint32_t roff = ST_R + ((ln >> 1) & 3) * 16 + (ln >> 3) * 4 + (ln & 1) * 2;
    const unsigned char* ghot = smem + (MS_GH - HOT0 * 32);
    const unsigned char* gcold = reinterpret_cast<const unsigned char*>(g_G);
    asm volatile("" : "+l"(ghot), "+l"(gcold));
    const int total = (int)__reduce_or_sync(0xffffffffu, (uint32_t)b2[NBIN]);
    const int half = total >> 1;
    const int ulo = un ? half : 0, uhi = un ? total : half;
    const int nnodes = min(NPC, N - (int)blockIdx.x * NPC);
    uint32_t todo;
    {
        const int beg = b2[min(ln, NQ) * NCTA], end = b2[min(ln + 1, NQ) * NCTA];
        todo = __ballot_sync(0xffffffffu, ln < NQ && (un ? (beg >= half || end > half) : beg < half));
    }
    uint32_t k = pw >> 1 ? 0xffffffffu : 0u;
    const uint32_t kb = pw >> 1;
    do {
        const int q = todo ? __ffs(todo) - 1 : 0;
        const bool none = todo == 0;
        todo &= todo - 1;
        const int beg = (int)__reduce_or_sync(0xffffffffu, (uint32_t)b2[q * NCTA]);
        const int ge = (int)__reduce_or_sync(0xffffffffu, (uint32_t)b2[(q + 1) * NCTA]);
        const bool own = beg >= ulo && !none;
        const int lo = max(beg, ulo), hi = min(ge, uhi);
        int rem = none ? 0 : hi - lo;
        const int lastcap = own ? 24 : 32;
        const uint32_t flast = ((uint32_t)q << 8) | (none ? 0u : own ? (ge > uhi ? 18u : 2u) : 4u) | (todo ? 0u : 8u);
        bool last;
        do {
            last = rem <= lastcap;
            if (!(k & 1u)) {
                const bool valid = ln < rem;
                const bool svl = last && own;
                uint2 r = make_uint2(0, 0);
                if (FITS) {
                    asm volatile("ld.shared.v2.u32 {%0,%1}, [%2];" : "=r"(r.x), "=r"(r.y) : "r"(sbase + MS_REC + (hi - rem + ln) * 8));
                    if (!valid) r = make_uint2(0, 0);
                } else if (valid) {
                    const int j = hi - rem + ln;
                    const int* prq = b2 + q * NCTA;
                    int l0 = 0, up = NCTA;
                    while (up - l0 > 1) {
                        const int mid = (l0 + up) >> 1;
                        if (prq[mid] <= j) l0 = mid; else up = mid;
                    }
                    const int b0 = __ldcg(reinterpret_cast<const unsigned short*>(g_pfx + (l0 * NCTA + blockIdx.x) * 2) + q + (q >= 7));
                    r = __ldcg(g_rec + l0 * CH + b0 + (j - prq[l0]));
                }
                const uint32_t srcv = (r.y >> 16) & 0x7fffu;
                const unsigned char* gq[8];
#pragma unroll
                for (int i = 0; i < 8; i++)
                    gq[i] = gsrc + (size_t)__shfl_sync(0xffffffffu, srcv, i * 4 + r4) * ROWB;
                const int lim = rem - r4;
                int lim6 = lim;
                if (svl) {
                    gq[6] = reinterpret_cast<const unsigned char*>(sv) + (size_t)(blockIdx.x * NPC + q * GRP + r4) * 512 + (ln & 7) * 16;
                    gq[7] = gq[6] + 4 * 512;
                    lim6 = nnodes - q * GRP + 24 - r4;
                }
                const uint32_t rxy = hmul2(r.x & 0x9fff9fffu, 0x60806080u);
                const uint32_t rz2 = hmul2(r.y & 0x00009fffu, 0x60806080u);
                const uint32_t qxy = hmul2(rxy, rxy), qz = hmul2(rz2, rz2);
                const float sum = bf16r((__uint_as_float(qxy << 16) + __uint_as_float(qxy & 0xffff0000u)) + __uint_as_float(qz << 16));
                float sq;
                asm("sqrt.approx.ftz.f32 %0, %1;" : "=f"(sq) : "f"(bf16r(sum + 1e-8f)));
                const uint32_t dbits = pack_bf16(0.f, sq);
                float rinv;
                asm("rcp.approx.ftz.f32 %0, %1;" : "=f"(rinv) : "f"(__uint_as_float(dbits)));
                const int di = valid ? max(min((int)(dbits >> 16), DEND - 1) - DBASE, 0) : NTAB - 1;
                const uint4* gp = reinterpret_cast<const uint4*>(di >= HOT0 ? ghot : gcold) + 2 * di;
                const uint32_t r01 = pack_bf16(__uint_as_float(rxy << 16) * rinv, __uint_as_float(rxy & 0xffff0000u) * rinv);
                const uint32_t r2 = pack_bf16(__uint_as_float(rz2 << 16) * rinv, valid ? 1.0f : 0.f);
                const uint32_t so = ((r.x >> 12) & 6u) | ((r.x >> 26) & 8u);

                const uint32_t sb = ubase + ((k + kb) & (STAGES - 1)) * STAGE_BYTES;
                const uint32_t bar = sb + ST_CTL;
                mbar_wait(bar + 8, (((k + kb) >> 2) & 1u) ^ 1u);
                const uint32_t dpa = sb + d0, dpb = (dpa ^ 64u) + 512u;
#pragma unroll
                for (int i = 0; i < 8; i++) {
                    asm volatile("{\n.reg .pred p;\nsetp.le.s32 p, %2, %3;\n"
                                 "cp.async.cg.shared.global [%0], [%1], 16, p;\n"
                                 "cp.async.cg.shared.global [%0+4096], [%1+128], 16, p;\n"
                                 "cp.async.cg.shared.global [%0+8192], [%1+256], 16, p;\n"
                                 "cp.async.cg.shared.global [%0+12288], [%1+384], 16, p;\n}\n"
                                 ::"r"(((i & 1) ? dpb : dpa) + (i >> 1) * 1024), "l"(gq[i]), "r"(i < 6 ? lim : lim6), "r"(4 * i) : "memory");
                }
                asm volatile("cp.async.mbarrier.arrive.noinc.shared::cta.b64 [%0];" ::"r"(bar) : "memory");
                const uint4 g0 = gp[0], g1 = gp[1];
                const uint32_t za = sb + ST_S + ln * 16;
                asm volatile("st.shared.v4.u32 [%0], {%1,%1,%1,%1};" ::"r"(za), "r"(0u) : "memory");
                asm volatile("st.shared.u16 [%0], %1;" ::"r"(za + so), "h"((unsigned short)(r2 >> 16)) : "memory");
                asm volatile("st.shared.u16 [%0], %1;" ::"r"(sb + roff), "h"((unsigned short)(r01 & 0xffffu)) : "memory");
                asm volatile("st.shared.u16 [%0+64], %1;" ::"r"(sb + roff), "h"((unsigned short)(r01 >> 16)) : "memory");
                asm volatile("st.shared.u16 [%0+128], %1;" ::"r"(sb + roff), "h"((unsigned short)(r2 & 0xffffu)) : "memory");
                asm volatile("st.shared.u32 [%0+16], %1;" ::"r"(bar), "r"(last ? flast : 0u) : "memory");
                asm volatile("st.shared.v4.u32 [%0], {%1,%2,%3,%4};" ::"r"(sb + goff),
                             "r"(g0.x), "r"(g0.y), "r"(g0.z), "r"(g0.w) : "memory");
                asm volatile("st.shared.v4.u32 [%0], {%1,%2,%3,%4};" ::"r"((sb + goff) ^ 16u),
                             "r"(g1.x), "r"(g1.y), "r"(g1.z), "r"(g1.w) : "memory");
                asm volatile("fence.proxy.async.shared::cta;" ::: "memory");
                mbar_arrive(bar);
            }
            k++;
            rem -= 32;
        } while (!last);
    } while (todo);
    if (!(k & 1u)) {
        const uint32_t bar = ubase + ((k + kb) & (STAGES - 1)) * STAGE_BYTES + ST_CTL;
        mbar_wait(bar + 8, (((k + kb) >> 2) & 1u) ^ 1u);
        mbar_arrive(bar);
        mbar_arrive(bar);
    }
}

__global__ void __launch_bounds__(M_THREADS, 1)
fused_kernel(const __nv_bfloat16* __restrict__ sv, const __nv_bfloat16* __restrict__ pos,
             const int* __restrict__ src, const int* __restrict__ dst,
             const __nv_bfloat16* __restrict__ freqs, const __nv_bfloat16* __restrict__ w1,
             const __nv_bfloat16* __restrict__ w2, const __nv_bfloat16* __restrict__ wrbf,
             __nv_bfloat16* __restrict__ out, int N, int E) {
    extern __shared__ __align__(1024) unsigned char smem[];
    const int tid = threadIdx.x, lane = tid & 31;
    const int warp = (int)__reduce_or_sync(0xffffffffu, (uint32_t)tid >> 5);
    const uint32_t sbase = smem_u32(smem);
    const uint32_t ghbar = sbase + MS_BAR;
    const bool is_prod = warp >= 12;
    const int cta = blockIdx.x;
    const int nnodes = min(NPC, N - cta * NPC);

    STAMP(0, 0);
    unsigned int epoch;
    asm volatile("ld.relaxed.gpu.global.u32 %0, [%1];" : "=r"(epoch) : "l"(&g_cnt));
    unsigned short freq_bits;
    asm volatile("ld.global.nc.u16 %0, [%1];" : "=h"(freq_bits) : "l"(freqs + (tid & 15)));
    const int npair = max(min(EPC, E - cta * EPC), 0) >> 1;
#pragma unroll 1
    for (int i = tid; i < (N * 6 + 15) / 16; i += M_THREADS)
        cp_async16(sbase + PS_POS + i * 16, reinterpret_cast<const unsigned char*>(pos) + i * 16);
    asm volatile("cp.async.commit_group;" ::: "memory");
#pragma unroll 1
    for (int k = 0, i = tid; k < 5; k++, i += M_THREADS) {
        if (i < npair) {
            asm volatile("cp.async.ca.shared.global [%0], [%1], 8;" ::"r"(sbase + PS_SRC + i * 8), "l"(src + cta * EPC + 2 * i) : "memory");
            asm volatile("cp.async.ca.shared.global [%0], [%1], 8;" ::"r"(sbase + PS_DST + i * 8), "l"(dst + cta * EPC + 2 * i) : "memory");
        }
        asm volatile("cp.async.commit_group;" ::: "memory");
    }
    int* hist = reinterpret_cast<int*>(smem + PS_HIST);
    int* b2 = reinterpret_cast<int*>(smem + MS_B2);
    if (tid < 384) {
        reinterpret_cast<int4*>(hist)[tid] = make_int4(0, 0, 0, 0);
        reinterpret_cast<int4*>(b2)[tid] = make_int4(0, 0, 0, 0);
    }
    asm volatile("cp.async.wait_group 5;" ::: "memory");
    __syncthreads();
    STAMP(1, 0);
#pragma unroll 1
    for (int i = tid; i < 96 * 32; i += M_THREADS) {
        const int node = i >> 5, row = node & 31;
        asm volatile("{\n.reg .pred p;\nsetp.ge.s32 p, %2, %3;\ncp.async.cg.shared.global [%0], [%1], 16, p;\n}\n"
                     ::"r"(sbase + (node >> 5) * STAGE_BYTES + (lane >> 3) * 4096 + row * 128 + (((lane ^ row) & 7) << 4)),
                       "l"(sv + (size_t)(cta * NPC + min(node, nnodes - 1)) * 256 + lane * 8), "r"(node), "r"(nnodes) : "memory");
    }
    {
        const int r = tid >> 3, c = tid & 7;
        const uint32_t o = sbase + PS_W1 + r * 128 + (((c ^ r) & 7) << 4);
        cp_async16(o, w1 + tid * 8);
        cp_async16(o + 8192, w2 + r * 192 + 64 + c * 8);
        cp_async16(sbase + PS_W2 + r * 272 + c * 16, w2 + r * 192 + c * 8);
        cp_async16(sbase + PS_W2 + r * 272 + 128 + c * 16, w2 + r * 192 + 128 + c * 8);
        if (tid < 384) cp_async16(sbase + PS_WR + (tid / 24) * 400 + (tid % 24) * 16, wrbf + tid * 8);
    }
    {
        int2* ps = reinterpret_cast<int2*>(smem + PS_SRC);
        int2* pd = reinterpret_cast<int2*>(smem + PS_DST);
        int2* pk = reinterpret_cast<int2*>(smem + PS_KEY);
#pragma unroll 1
        for (int i = tid; i < npair; i += M_THREADS) {
            asm volatile("cp.async.commit_group;\ncp.async.wait_group 5;" ::: "memory");
            const int2 es = ps[i], ed = pd[i];
            int rx[2], ry[2], key[2];
#pragma unroll
            for (int b = 0; b < 2; b++) {
                const uint32_t sn = b ? es.y : es.x, dn = b ? ed.y : ed.x;
                const uint32_t as = sbase + PS_POS + sn * 6, ad = sbase + PS_POS + dn * 6;
                uint32_t sa, sb, da, db;
                asm volatile("ld.shared.u32 %0, [%2];\nld.shared.u32 %1, [%2+4];" : "=r"(sa), "=r"(sb) : "r"(as & ~3u));
                asm volatile("ld.shared.u32 %0, [%2];\nld.shared.u32 %1, [%2+4];" : "=r"(da), "=r"(db) : "r"(ad & ~3u));
                const uint32_t rxy = hsub2(__funnelshift_r(sa, sb, as << 3), __funnelshift_r(da, db, ad << 3));
                const uint32_t rz = hsub2(__funnelshift_r(sb, 0u, as << 3), __funnelshift_r(db, 0u, ad << 3));
                const uint32_t qxy = hmul2(rxy, rxy), qz = hmul2(rz, rz);
                const float sum = (__uint_as_float(qxy << 16) + __uint_as_float(qxy & 0xffff0000u)) + __uint_as_float(qz << 16);
                const uint32_t c = dn / NPC, dl = dn - c * NPC;
                rx[b] = hmul2(rxy, 0x1e801e80u) | ((dl * 0x08002000u) & 0x60006000u);
                ry[b] = __byte_perm(hmul2(rz, 0x1e801e80u), sn, 0x5410) | ((dl * 0x02000200u) & 0x80006000u);
                const uint32_t ba = sbase + PS_HIST + (c * NQ + (dl >> 3)) * 4;
                asm volatile("{\n.reg .pred p;\nsetp.lt.f32 p, %2, 0f41BF8000;\nmov.u32 %0, 0x80000000;\n"
                             "@p atom.shared.add.u32 %0, [%1], 1;\n}\n" : "=r"(key[b]) : "r"(ba), "f"(sum) : "memory");
                key[b] |= ba << 13;
            }
            ps[i] = make_int2(rx[0], rx[1]);
            pd[i] = make_int2(ry[0], ry[1]);
            pk[i] = make_int2(key[0], key[1]);
        }
        STAMP(18, 0);
        asm volatile("cp.async.wait_all;" ::: "memory");
        asm volatile("fence.proxy.async.shared::cta;" ::: "memory");
        __syncthreads();
        STAMP(2, 0);
        if (is_prod) {
            const int pt = tid - 384;
            scan1536(hist, pt);
            STAMP(16, 384);
#pragma unroll 1
            for (int gi = cta * 256 + pt; gi < min(cta * 256 + 256, NTAB * NRBF); gi += 128) {
                const float d = __uint_as_float((uint32_t)(DBASE + (gi >> 4)) << 16);
                const float arg = bf16r(d * __uint_as_float((uint32_t)freq_bits << 16));
                float sn;
                if (fabsf(arg) < 1000.f) {
                    const float k = rintf(arg * 0.15915494309189535f);
                    sn = __sinf(fmaf(k, 1.7484556000744883e-7f, fmaf(k, -6.2831854820251465f, arg)));
                } else {
                    sn = sinf(arg);
                }
                const float rbf = bf16r(__fdividef(bf16r(sn), d));
                const float ca = bf16r(bf16r(3.14159265358979f * d) * 0.2f);
                const float fc = 0.5f * bf16r(bf16r(__cosf(ca)) + 1.0f);
                g_G[gi] = __float2bfloat16_rn(rbf * fc);
            }
            if (pt < 2) mbar_init(ghbar + 8 + pt * 8, 128);
            STAMP(17, 384);
        } else {
            const uint32_t tb = sbase + (warp >> 2) * STAGE_BYTES;
            const uint32_t fo = ((lane & 7) + 8 * (lane >> 4)) * 128 + ((uint32_t)((2 * (warp & 3) + ((lane >> 3) & 1)) ^ (lane & 7)) << 4);
            const uint32_t dh = (tb >> 4) | (1u << 16);
            uint32_t x[2][4];
#pragma unroll 1
            for (int it = 0; it < 2; it++) {
                uint32_t a[4][4];
                float d[16];
#pragma unroll
                for (int q = 0; q < 4; q++) ldsm4t(a[q], sbase + PS_W1 + it * 8192 + q * 2048 + fo);
                asm volatile("wgmma.fence.sync.aligned;" ::: "memory");
                wgmma_n32<0, DESC_H>(d, a[0], dh);
                wgmma_n32<1, DESC_H>(d, a[1], dh + 2);
                wgmma_n32<1, DESC_H>(d, a[2], dh + 4);
                wgmma_n32<1, DESC_H>(d, a[3], dh + 6);
                asm volatile("wgmma.commit_group.sync.aligned;" ::: "memory");
                asm volatile("wgmma.wait_group.sync.aligned 0;" ::: "memory");
                reg_fence16(d);
#pragma unroll
                for (int i = 0; i < 8; i++) x[i >> 2][i & 3] = pack_bf16(d[2 * i], d[2 * i + 1]);
                if (it) break;
                asm volatile("bar.sync %0, 128;" ::"r"(1 + (warp >> 2)) : "memory");
#pragma unroll 1
                for (int s = 0; s < 2; s++) {
                    uint32_t y[4];
#pragma unroll
                    for (int e = 0; e < 4; e++) {
                        const float z0 = __uint_as_float(x[0][e] << 16), z1 = __uint_as_float(x[0][e] & 0xffff0000u);
                        float e0, e1;
                        asm("ex2.approx.ftz.f32 %0, %1;" : "=f"(e0) : "f"(z0 * -1.4426950408889634f));
                        asm("ex2.approx.ftz.f32 %0, %1;" : "=f"(e1) : "f"(z1 * -1.4426950408889634f));
                        asm("rcp.approx.ftz.f32 %0, %1;" : "=f"(e0) : "f"(e0 + 1.0f));
                        asm("rcp.approx.ftz.f32 %0, %1;" : "=f"(e1) : "f"(e1 + 1.0f));
                        y[e] = pack_bf16(z0 * e0, z1 * e1);
                        x[0][e] = x[1][e];
                    }
                    stsm4t(tb + fo + s * 2048, y);
                }
                asm volatile("fence.proxy.async.shared::cta;" ::: "memory");
                asm volatile("bar.sync %0, 128;" ::"r"(1 + (warp >> 2)) : "memory");
                STAMP(14, 0);
            }
#pragma unroll 1
            for (int j = 1; j < 4; j++) {
                uint32_t v[2][4];
                ldsm4t(v[0], tb + fo + j * 4096);
                ldsm4t(v[1], tb + fo + j * 4096 + 2048);
#pragma unroll
                for (int e = 0; e < 8; e++) v[e >> 2][e & 3] = hmul2(v[e >> 2][e & 3], x[e >> 2][e & 3]);
                stsm4t(tb + fo + j * 4096, v[0]);
                stsm4t(tb + fo + j * 4096 + 2048, v[1]);
            }
            STAMP(15, 0);
        }
        __syncthreads();
        STAMP(3, 0);
#pragma unroll 2
        for (int node = warp; node < nnodes; node += 16) {
            const int row = node & 31;
            reinterpret_cast<uint4*>(g_tab + (size_t)(cta * NPC + node) * ROWB)[lane] = *reinterpret_cast<const uint4*>(
                smem + (node >> 5) * STAGE_BYTES + (lane >> 3) * 4096 + row * 128 + (((lane ^ row) & 7) << 4));
        }
        STAMP(8, 0);
#pragma unroll 1
        for (int i = tid; i < npair; i += M_THREADS) {
            const int2 k = pk[i], x = ps[i], y = pd[i];
            int o0, o1;
            asm volatile("ld.shared.u32 %0, [%1];" : "=r"(o0) : "r"((k.x >> 13) & 0x3ffff));
            asm volatile("ld.shared.u32 %0, [%1];" : "=r"(o1) : "r"((k.y >> 13) & 0x3ffff));
            int2* sorted = reinterpret_cast<int2*>(smem + PS_POS);
            if (k.x >= 0) sorted[o0 + (k.x & 8191)] = make_int2(x.x, y.x);
            if (k.y >= 0) sorted[o1 + (k.y & 8191)] = make_int2(x.y, y.y);
        }
        __syncthreads();
        STAMP(4, 0);
        const int n16 = (hist[NBIN] + 1) >> 1;
#pragma unroll 1
        for (int i = tid; i < n16; i += M_THREADS)
            reinterpret_cast<uint4*>(g_rec + cta * CH)[i] = reinterpret_cast<const uint4*>(smem + PS_POS)[i];
        __syncthreads();
        STAMP(5, 0);
    }
    unsigned short* pf = reinterpret_cast<unsigned short*>(smem + PS_PF);
    {
        const uint32_t tag = ((epoch / NCTA + 1) & 0xffffu) << 16;
        if (warp < 9) {
            const int c = min(tid >> 1, NCTA - 1);
            const int* h = hist + c * NQ + (tid & 1) * 7;
            uint4 v = make_uint4(h[0] | (h[1] << 16), h[2] | (h[3] << 16), h[4] | (h[5] << 16), h[6] | tag);
            __threadfence();
            asm volatile("st.relaxed.gpu.global.v4.u32 [%0], {%1,%2,%3,%4};" ::"l"(g_pfx + (cta * NCTA + c) * 2 + (tid & 1)),
                         "r"(v.x), "r"(v.y), "r"(v.z), "r"(v.w) : "memory");
        } else if (warp == 15) {
            if (lane < 2 * UNITS * STAGES) mbar_init(sbase + (lane >> 1) * STAGE_BYTES + ST_CTL + (lane & 1) * 8, (lane & 1) ? 4 : 64);
            if (lane == 31) atomicInc(&g_cnt, NCTA * 65536u - 1);
        }
        STAMP(6, 0);
        const int p = min(warp + 16 * (lane >> 1), NCTA - 1);
        uint4 v;
        int spin = 0;
        do {
            asm volatile("ld.acquire.gpu.global.v4.u32 {%0,%1,%2,%3}, [%4];" : "=r"(v.x), "=r"(v.y), "=r"(v.z), "=r"(v.w)
                         : "l"(g_pfx + (p * NCTA + cta) * 2 + (lane & 1)) : "memory");
        } while (__any_sync(0xffffffffu, (v.w ^ tag) & 0xffff0000u) && ++spin < (1 << 22));
        STAMP(7, 0);
        reinterpret_cast<uint4*>(pf)[p * 2 + (lane & 1)] = v;
#pragma unroll 1
        for (int k = 0, pp = warp; pp < NCTA; k += 2, pp += 16) {
            const int i = (__shfl_sync(0xffffffffu, v.x, k) & 0xfffe) + 2 * lane;
            const int e = __shfl_sync(0xffffffffu, v.y, k + 1) >> 16;
            if (i < e) cp_async16(sbase + (3 + (pp >> 5)) * STAGE_BYTES + (pp & 31) * 512 + lane * 16, g_rec + pp * CH + i);
        }
        __syncwarp();
#pragma unroll 1
        for (int e = lane; e < 96; e += 32) {
            const int k = e / NQ, q = e - k * NQ, pp = warp + 16 * k;
            if (pp < NCTA) b2[q * NCTA + pp] = pf[pp * 16 + q + 1 + (q >= 6)] - pf[pp * 16 + q + (q >= 7)];
        }
        __syncthreads();
        STAMP(9, 0);
        if (is_prod) {
            scan1536(b2, tid - 384);
        } else {
#pragma unroll 1
            for (int i = tid; i < (NTAB - HOT0) * 2; i += 384) cp_async16(sbase + MS_GH + i * 16, g_G + HOT0 * NRBF + i * 8);
        }
        asm volatile("cp.async.wait_all;" ::: "memory");
    }
    __syncthreads();
    STAMP(11, 0);
    if (b2[NBIN] <= RCAP) {
        uint2* srec = reinterpret_cast<uint2*>(smem + MS_REC);
#pragma unroll 1
        for (int p = 2 * warp + (lane >> 4); p < NCTA; p += 32) {
            const int beg = pf[p * 16], end = pf[p * 16 + NQ + 1];
            const uint4* raw = reinterpret_cast<const uint4*>(smem + (3 + (p >> 5)) * STAGE_BYTES + (p & 31) * 512);
#pragma unroll 1
            for (int o = lane & 15, i = (beg & ~1) + 2 * o; i < end; o += 16, i += 32) {
                const uint4 v = o < 32 ? raw[o] : __ldcg(reinterpret_cast<const uint4*>(g_rec + p * CH + i));
                const int q0 = (int)(((v.x >> 30) & 1u) | ((v.y >> 12) & 6u) | ((v.y >> 28) & 8u));
                const int q1 = (int)(((v.z >> 30) & 1u) | ((v.w >> 12) & 6u) | ((v.w >> 28) & 8u));
                if (i >= beg) srec[b2[q0 * NCTA + p] - pf[p * 16 + q0 + (q0 >= 7)] + i] = make_uint2(v.x, v.y);
                if (i + 1 < end) srec[b2[q1 * NCTA + p] - pf[p * 16 + q1 + (q1 >= 7)] + i + 1] = make_uint2(v.z, v.w);
            }
        }
    }
    __syncthreads();
    STAMP(12, 0);

    if (warp >= 12) {
        asm volatile("setmaxnreg.dec.sync.aligned.u32 24;");
    } else if (warp >= 8) {
        asm volatile("setmaxnreg.dec.sync.aligned.u32 72;");
        asm volatile("bar.sync 6, 384;" ::: "memory");
        STAMP(21, 256);
        if (__reduce_or_sync(0xffffffffu, (uint32_t)b2[NBIN]) <= RCAP) producer_loop<true>(smem, sv, N, warp - 8);
        else producer_loop<false>(smem, sv, N, warp - 8);
        GSTAMP(22 + (warp & 1), 256 + 32 * (warp & 1));
    } else {
        asm volatile("setmaxnreg.inc.sync.aligned.u32 208;");
        const int unit = warp >> 2, w = warp & 3;
        uint32_t wa[3][4], pa[2][4][4];
        {
            const int krow = (lane & 7) + 8 * (lane >> 4), mcol = 2 * w + ((lane >> 3) & 1);
#pragma unroll
            for (int q = 0; q < 4; q++) {
                ldsm4t(pa[0][q], sbase + PS_W2 + (16 * q + krow) * 272 + mcol * 16);
                ldsm4t(pa[1][q], sbase + PS_W2 + (16 * q + krow) * 272 + 128 + mcol * 16);
            }
#pragma unroll
            for (int p = 0; p < 3; p++) ldsm4t(wa[p], sbase + PS_WR + krow * 400 + p * 128 + mcol * 16);
            asm volatile("bar.arrive 6, 384;" ::: "memory");
        }
        float acc[4][4];
#pragma unroll
        for (int i = 0; i < 16; i++) acc[i >> 2][i & 3] = 0.f;
        const uint32_t ua = pin(4096 + ((lane & 7) + 8 * (lane >> 4)) * 128 + ((uint32_t)((2 * w + ((lane >> 3) & 1)) ^ (lane & 7)) << 4));
        const uint32_t ra = pin(ST_R + (lane & 3) * 16);
        const uint32_t sa = pin(ST_S + lane * 16);
        const uint32_t ub = sbase + unit * STAGES * STAGE_BYTES;
        float pr[16], fr[16], fv[16], ps[16], fs[16];
        auto issue = [&](uint32_t sn) {
            const uint32_t dh = (sn >> 4) | (1u << 16);
            const uint32_t dg = dh + (ST_G >> 4);
            asm volatile("wgmma.fence.sync.aligned;" ::: "memory");
            wgmma_n32<0, DESC_G>(fr, wa[2], dg);
            wgmma_n32<0, DESC_H>(pr, pa[1][0], dh);
            wgmma_n32<0, DESC_H>(ps, pa[0][0], dh);
            wgmma_n32<1, DESC_H>(pr, pa[1][1], dh + 2);
            wgmma_n32<1, DESC_H>(ps, pa[0][1], dh + 2);
            wgmma_n32<1, DESC_H>(pr, pa[1][2], dh + 4);
            wgmma_n32<1, DESC_H>(ps, pa[0][2], dh + 4);
            wgmma_n32<1, DESC_H>(pr, pa[1][3], dh + 6);
            wgmma_n32<1, DESC_H>(ps, pa[0][3], dh + 6);
            wgmma_n32<0, DESC_G>(fv, wa[1], dg);
            wgmma_n32<0, DESC_G>(fs, wa[0], dg);
            asm volatile("wgmma.commit_group.sync.aligned;" ::: "memory");
        };
        mbar_wait(ub + ST_CTL, 0);
        issue(ub);
        uint32_t k = 0;
        while (true) {
            const uint32_t sb = ub + (k & (STAGES - 1)) * STAGE_BYTES;
            k++;
            const uint32_t sn = ub + (k & (STAGES - 1)) * STAGE_BYTES;
            uint32_t ms[2][4], mr[2][4], wv[2][4];
            asm volatile("wgmma.wait_group.sync.aligned 0;" ::: "memory");
            reg_fence16(pr); reg_fence16(fr); reg_fence16(fv); reg_fence16(ps); reg_fence16(fs);
#pragma unroll
            for (int i = 0; i < 8; i++) {
                mr[i >> 2][i & 3] = pack_bf16(fr[2 * i] * pr[2 * i], fr[2 * i + 1] * pr[2 * i + 1]);
                ms[i >> 2][i & 3] = pack_bf16(fs[2 * i] * ps[2 * i], fs[2 * i + 1] * ps[2 * i + 1]);
                wv[i >> 2][i & 3] = pack_bf16(fv[2 * i], fv[2 * i + 1]);
            }
            mbar_wait(sn + ST_CTL, (k >> 2) & 1u);
            issue(sn);
            asm volatile("wgmma.wait_group.sync.aligned 1;" ::: "memory");
            uint32_t u[2][3][4];
#pragma unroll
            for (int j = 0; j < 3; j++) {
                uint32_t rr[4];
                ldsm4t(u[0][j], sb + ua + j * 4096);
                ldsm4t(u[1][j], sb + ua + j * 4096 + 2048);
                asm volatile("ld.shared.v4.u32 {%0,%1,%2,%3}, [%4];" : "=r"(rr[0]), "=r"(rr[1]), "=r"(rr[2]), "=r"(rr[3]) : "r"(sb + ra + j * 64));
#pragma unroll
                for (int e = 0; e < 8; e++)
                    u[e >> 2][j][e & 3] = hfma2(mr[e >> 2][e & 3], rr[e >> 1], hmul2(u[e >> 2][j][e & 3], wv[e >> 2][e & 3]));
            }
#pragma unroll
            for (int j = 0; j < 6; j++)
                asm volatile("{\n.reg .pred p;\nsetp.lt.s32 p, %5, 0;\n@p st.shared.v4.u32 [%0], {%1,%2,%3,%4};\n}\n"
                             ::"r"(ra), "r"(u[j & 1][j >> 1][0]), "r"(u[j & 1][j >> 1][1]), "r"(u[j & 1][j >> 1][2]), "r"(u[j & 1][j >> 1][3]), "r"(N) : "memory");
            uint32_t sf[4], flags;
            ldsm4t(sf, sb + sa);
            asm volatile("ld.shared.u32 %0, [%1+16];" : "=r"(flags) : "r"(sb + ST_CTL));
#pragma unroll
            for (int s = 0; s < 2; s++) {
                mma16816(acc[0], ms[s], sf[2 * s], sf[2 * s + 1]);
#pragma unroll
                for (int j = 0; j < 3; j++) mma16816(acc[j + 1], u[s][j], sf[2 * s], sf[2 * s + 1]);
            }
            if (flags & 6u) {
                float* part = reinterpret_cast<float*>(smem + MS_PART) + (tid & 127);
                if (flags & 4u) {
#pragma unroll
                    for (int i = 0; i < 16; i++) part[i * 128] = acc[i >> 2][i & 3];
                    mbar_arrive(sbase + MS_BAR + 8);
                } else {
                    if (flags & 16u) {
                        mbar_wait(sbase + MS_BAR + 8, 0);
#pragma unroll
                        for (int i = 0; i < 16; i++) acc[i >> 2][i & 3] += part[i * 128];
                    }
                    const uint32_t ea = sb + (lane >> 4) * 4096 + (24 + (lane & 7)) * 128 +
                                        ((uint32_t)((2 * w + ((lane >> 3) & 1)) ^ (lane & 7)) << 4);
#pragma unroll
                    for (int kk = 0; kk < 2; kk++) {
                        uint32_t v[4];
                        ldsm4t(v, ea + kk * 8192);
#pragma unroll
                        for (int e = 0; e < 4; e++)
                            v[e] = pack_bf16(__uint_as_float(v[e] << 16) + acc[2 * kk + (e >> 1)][2 * (e & 1)],
                                             __uint_as_float(v[e] & 0xffff0000u) + acc[2 * kk + (e >> 1)][2 * (e & 1) + 1]);
                        stsm4t(ea + kk * 8192, v);
                    }
                    __syncwarp();
                    const int ln0 = (int)(flags >> 8) * GRP + (lane >> 2);
                    const int c0 = (lane >> 1) & 1, ch = 2 * w + (lane & 1);
                    uint4* op = reinterpret_cast<uint4*>(out + (size_t)(blockIdx.x * NPC + ln0) * 256) + c0 * 8 + ch;
                    const uint32_t ia = sb + c0 * 4096 + (24 + (lane >> 2)) * 128 + ((uint32_t)(ch ^ (lane >> 2)) << 4);
#pragma unroll
                    for (int kk = 0; kk < 2; kk++) {
                        asm volatile("{\n.reg .pred p;\n.reg .b32 a, b, c, d;\nsetp.lt.s32 p, %2, %3;\n"
                                     "ld.shared.v4.u32 {a, b, c, d}, [%0];\n"
                                     "@p st.global.v4.u32 [%1], {a, b, c, d};\n}\n"
                                     ::"r"(ia + kk * 8192), "l"(op + kk * 16), "r"(ln0), "r"(min(NPC, N - (int)blockIdx.x * NPC)) : "memory");
                    }
                }
#pragma unroll
                for (int i = 0; i < 16; i++) acc[i >> 2][i & 3] = 0.f;
            }
            if (flags & 8u) break;
            asm volatile("{\n.reg .pred p;\nelect.sync _|p, 0xffffffff;\n@p mbarrier.arrive.shared::cta.b64 _, [%0];\n}\n"
                         ::"r"(sb + ST_CTL + 8) : "memory");
        }
        asm volatile("wgmma.wait_group.sync.aligned 0;" ::: "memory");
        reg_fence16(pr); reg_fence16(fr); reg_fence16(fv); reg_fence16(ps); reg_fence16(fs);
        GSTAMP(26 + unit, 128 * unit);
    }
}

}

extern "C" void kernel_launch(void* const* d_in, const int* in_sizes, int n_in, void* d_out, int out_size) {
    const __nv_bfloat16* sv = (const __nv_bfloat16*)d_in[0];
    const __nv_bfloat16* pos = (const __nv_bfloat16*)d_in[1];
    const int* src = (const int*)d_in[2];
    const int* dst = (const int*)d_in[3];
    const __nv_bfloat16* freqs = (const __nv_bfloat16*)d_in[4];
    const __nv_bfloat16* w1 = (const __nv_bfloat16*)d_in[5];
    const __nv_bfloat16* w2 = (const __nv_bfloat16*)d_in[6];
    const __nv_bfloat16* wrbf = (const __nv_bfloat16*)d_in[7];
    __nv_bfloat16* out = (__nv_bfloat16*)d_out;
    const int N = in_sizes[1] / 3;
    const int E = in_sizes[2];

    static bool init = false;
    if (!init) {
        cudaFuncSetAttribute(fused_kernel, cudaFuncAttributeMaxDynamicSharedMemorySize, M_SMEM);
        init = true;
    }
    fused_kernel<<<NCTA, M_THREADS, M_SMEM, cudaStreamPerThread>>>(sv, pos, src, dst, freqs, w1, w2, wrbf, out, N, E);
}
```

```cpp
#include <cuda_runtime.h>
#include <cuda_bf16.h>
#include <stdint.h>

namespace {

constexpr int D = 64;
constexpr int NRBF = 16;
constexpr int MAXN = 10000;
constexpr int MAXE = 640000;
constexpr int NCTA = 132;
constexpr int GRP = 8;
constexpr int NPC = (MAXN + NCTA - 1) / NCTA;
constexpr int NQ = (NPC + GRP - 1) / GRP;
constexpr int NBIN = NCTA * NQ;
constexpr int CH = 4864;
constexpr int DBASE = 0x38C0;
constexpr int DEND = 0x40A0;
constexpr int NTAB = DEND - DBASE;
constexpr int TPC = 80;

__device__ __align__(128) unsigned char g_tab[(size_t)NCTA * TPC * 512];
__device__ __align__(128) __nv_bfloat16 g_G[NTAB * NRBF];
__device__ __align__(128) uint2 g_rec[NCTA * CH];
__device__ __align__(128) uint4 g_pfx[NCTA * NCTA * 2];
__device__ unsigned int g_cnt;

#define STAMP(k, tt) do {} while (0)
#define GSTAMP(k, tt) do {} while (0)

__device__ __forceinline__ uint32_t smem_u32(const void* p) { return (uint32_t)__cvta_generic_to_shared(p); }
__device__ __forceinline__ uint32_t pack_bf16(float lo, float hi) {
    uint32_t r;
    asm("cvt.rn.bf16x2.f32 %0, %1, %2;" : "=r"(r) : "f"(hi), "f"(lo));
    return r;
}
__device__ __forceinline__ float bf16r(float x) { return __uint_as_float(pack_bf16(0.f, x) & 0xffff0000u); }
__device__ __forceinline__ uint32_t hmul2(uint32_t a, uint32_t b) {
    uint32_t r;
    asm("mul.rn.bf16x2 %0, %1, %2;" : "=r"(r) : "r"(a), "r"(b));
    return r;
}
__device__ __forceinline__ uint32_t hsub2(uint32_t a, uint32_t b) {
    uint32_t r;
    asm("sub.rn.bf16x2 %0, %1, %2;" : "=r"(r) : "r"(a), "r"(b));
    return r;
}
__device__ __forceinline__ uint32_t hfma2(uint32_t a, uint32_t b, uint32_t c) {
    uint32_t r;
    asm("fma.rn.bf16x2 %0, %1, %2, %3;" : "=r"(r) : "r"(a), "r"(b), "r"(c));
    return r;
}
__device__ __forceinline__ void mma16816(float (&c)[4], const uint32_t (&a)[4], uint32_t b0, uint32_t b1) {
    asm volatile("mma.sync.aligned.m16n8k16.row.col.f32.bf16.bf16.f32 {%0,%1,%2,%3}, {%4,%5,%6,%7}, {%8,%9}, {%0,%1,%2,%3};"
                 : "+f"(c[0]), "+f"(c[1]), "+f"(c[2]), "+f"(c[3])
                 : "r"(a[0]), "r"(a[1]), "r"(a[2]), "r"(a[3]), "r"(b0), "r"(b1));
}
__device__ __forceinline__ void mma16816_z(float (&c)[4], const uint32_t (&a)[4], uint32_t b0, uint32_t b1) {
    asm volatile("mma.sync.aligned.m16n8k16.row.col.f32.bf16.bf16.f32 {%0,%1,%2,%3}, {%4,%5,%6,%7}, {%8,%9}, {%10,%10,%10,%10};"
                 : "=f"(c[0]), "=f"(c[1]), "=f"(c[2]), "=f"(c[3])
                 : "r"(a[0]), "r"(a[1]), "r"(a[2]), "r"(a[3]), "r"(b0), "r"(b1), "f"(0.f));
}
__device__ __forceinline__ void ldsm4(uint32_t (&r)[4], uint32_t addr) {
    asm volatile("ldmatrix.sync.aligned.m8n8.x4.shared.b16 {%0,%1,%2,%3}, [%4];"
                 : "=r"(r[0]), "=r"(r[1]), "=r"(r[2]), "=r"(r[3]) : "r"(addr));
}
__device__ __forceinline__ void ldsm4t(uint32_t (&r)[4], uint32_t addr) {
    asm volatile("ldmatrix.sync.aligned.m8n8.x4.trans.shared.b16 {%0,%1,%2,%3}, [%4];"
                 : "=r"(r[0]), "=r"(r[1]), "=r"(r[2]), "=r"(r[3]) : "r"(addr));
}
__device__ __forceinline__ void stsm4t(uint32_t addr, const uint32_t (&r)[4]) {
    asm volatile("stmatrix.sync.aligned.m8n8.x4.trans.shared.b16 [%0], {%1,%2,%3,%4};"
                 ::"r"(addr), "r"(r[0]), "r"(r[1]), "r"(r[2]), "r"(r[3]) : "memory");
}
__device__ __forceinline__ void cp_async16(uint32_t dst, const void* src) {
    asm volatile("cp.async.cg.shared.global [%0], [%1], 16;" ::"r"(dst), "l"(src) : "memory");
}
__device__ __forceinline__ void mbar_init(uint32_t bar, int cnt) {
    asm volatile("mbarrier.init.shared::cta.b64 [%0], %1;" ::"r"(bar), "r"(cnt) : "memory");
}
__device__ __forceinline__ void mbar_arrive(uint32_t bar) {
    asm volatile("mbarrier.arrive.shared::cta.b64 _, [%0];" ::"r"(bar) : "memory");
}
__device__ __forceinline__ void mbar_expect_tx(uint32_t bar, uint32_t bytes) {
    asm volatile("mbarrier.arrive.expect_tx.shared::cta.b64 _, [%0], %1;" ::"r"(bar), "r"(bytes) : "memory");
}
__device__ __forceinline__ void mbar_wait(uint32_t bar, uint32_t parity) {
    asm volatile(
        "{\n.reg .pred p;\n.reg .u32 n;\nmov.u32 n, 0;\n"
        "WAIT_%=:\n"
        "mbarrier.try_wait.parity.shared::cta.b64 p, [%0], %1, %2;\n"
        "@p bra DONE_%=;\n"
        "add.u32 n, n, 1;\n"
        "setp.lt.u32 p, n, 100000;\n"
        "@p bra WAIT_%=;\n"
        "exit;\n"
        "DONE_%=:\n}\n" ::"r"(bar), "r"(parity), "r"(10000u) : "memory");
}
__device__ __forceinline__ void mbar_wait_ft(uint32_t bar, uint32_t parity) {
    asm volatile(
        "{\n.reg .pred p;\n.reg .u32 n;\nmov.u32 n, 0;\n"
        "WAIT_%=:\n"
        "mbarrier.try_wait.parity.shared::cta.b64 p, [%0], %1, %2;\n"
        "@p bra DONE_%=;\n"
        "add.u32 n, n, 1;\n"
        "setp.lt.u32 p, n, 100000;\n"
        "@p bra WAIT_%=;\n"
        "DONE_%=:\n}\n" ::"r"(bar), "r"(parity), "r"(10000u) : "memory");
}
__device__ __forceinline__ void bulk_g2s(uint32_t dst, const void* src, uint32_t bytes, uint32_t bar) {
    asm volatile("cp.async.bulk.shared::cluster.global.mbarrier::complete_tx::bytes [%0], [%1], %2, [%3];"
                 ::"r"(dst), "l"(src), "r"(bytes), "r"(bar) : "memory");
}
__device__ __forceinline__ void bulk_s2g(void* dst, uint32_t src, uint32_t bytes) {
    asm volatile("cp.async.bulk.global.shared::cta.bulk_group [%0], [%1], %2;" ::"l"(dst), "r"(src), "r"(bytes) : "memory");
}

constexpr int UNITS = 2;
constexpr int STAGES = 4;
constexpr int M_THREADS = 512;
constexpr int ST_G = 4 * 4096;
constexpr int ST_S = ST_G + 1024;
constexpr int STAGE_BYTES = ST_S + 2048;
constexpr int RCAP = 3872;
constexpr int HOT0 = 0x3F00 - DBASE;
constexpr int MS_W2 = UNITS * STAGES * STAGE_BYTES;
constexpr int MS_REC = MS_W2 + 64 * 272;
constexpr int MS_PART = MS_REC + RCAP * 8;
constexpr int MS_GH = MS_PART + 8192;
constexpr int MS_B2 = MS_GH + (NTAB - HOT0) * 32;
constexpr int MS_MISC = MS_B2 + 1536 * 4;
constexpr int MS_BAR = MS_MISC + 32 * 4;
constexpr int MS_CTL = MS_BAR + 32;
constexpr int MS_DBG = MS_CTL + UNITS * STAGES * 32;
constexpr int M_SMEM = MS_DBG + 256;
constexpr int EPC = 4852;
constexpr int PS_TILE = 0;
constexpr int PS_POS = 49152;
constexpr int PS_W1 = PS_POS + 60416;
constexpr int PS_HIST = PS_W1 + 16384;
constexpr int PS_SRC = PS_HIST + (1536 + 32) * 4;
constexpr int PS_DST = MS_REC;
constexpr int PS_PF = PS_TILE;
constexpr int PS_DL = PS_PF + NCTA * 32;
constexpr int PS_W2 = MS_W2;
constexpr int PS_WR = MS_PART;
static_assert(PS_W1 % 128 == 0 && PS_PF % 16 == 0 && PS_DL + 1536 * 4 <= PS_POS && PS_SRC % 16 == 0 && PS_SRC + 5120 * 4 <= MS_W2 && 5120 * 4 <= RCAP * 8 &&
              EPC * NCTA >= MAXE && EPC <= CH && CH * 8 <= 60416 && EPC <= 5120, "phase-1 layout");
static_assert(M_SMEM <= 232448, "smem");
static_assert(MS_BAR % 8 == 0 && MS_GH % 16 == 0 && STAGE_BYTES % 1024 == 0, "align");

template <int ACC, uint32_t HI>
__device__ __forceinline__ void wgmma_n32(float (&d)[16], const uint32_t (&a)[4], uint32_t lo) {
    asm volatile("{\n.reg .b64 dd;\nmov.b64 dd, {%20, %21};\n"
                 "wgmma.mma_async.sync.aligned.m64n32k16.f32.bf16.bf16 {%0,%1,%2,%3,%4,%5,%6,%7,%8,%9,%10,%11,%12,%13,%14,%15}, {%16,%17,%18,%19}, dd, %22, 1, 1, 0;\n}\n"
                 : "+f"(d[0]), "+f"(d[1]), "+f"(d[2]), "+f"(d[3]), "+f"(d[4]), "+f"(d[5]), "+f"(d[6]), "+f"(d[7]),
                   "+f"(d[8]), "+f"(d[9]), "+f"(d[10]), "+f"(d[11]), "+f"(d[12]), "+f"(d[13]), "+f"(d[14]), "+f"(d[15])
                 : "r"(a[0]), "r"(a[1]), "r"(a[2]), "r"(a[3]), "r"(lo), "n"(HI), "n"(ACC));
}
__device__ __forceinline__ void wgmma_n8t(float (&d)[4], const uint32_t (&a)[4], uint32_t lo, uint32_t acc) {
    asm volatile("{\n.reg .b64 dd;\n.reg .pred p;\nsetp.ne.u32 p, %9, 0;\nmov.b64 dd, {%8, 32};\n"
                 "wgmma.mma_async.sync.aligned.m64n8k16.f32.bf16.bf16 {%0,%1,%2,%3}, {%4,%5,%6,%7}, dd, p, 1, 1, 1;\n}\n"
                 : "+f"(d[0]), "+f"(d[1]), "+f"(d[2]), "+f"(d[3]) : "r"(a[0]), "r"(a[1]), "r"(a[2]), "r"(a[3]), "r"(lo), "r"(acc));
}
__device__ __forceinline__ void wgmma_n24t(float (&d)[12], const uint32_t (&a)[4], uint32_t lo, uint32_t acc) {
    asm volatile("{\n.reg .b64 dd;\n.reg .pred p;\nsetp.ne.u32 p, %17, 0;\nmov.b64 dd, {%16, 32};\n"
                 "wgmma.mma_async.sync.aligned.m64n24k16.f32.bf16.bf16 {%0,%1,%2,%3,%4,%5,%6,%7,%8,%9,%10,%11}, {%12,%13,%14,%15}, dd, p, 1, 1, 1;\n}\n"
                 : "+f"(d[0]), "+f"(d[1]), "+f"(d[2]), "+f"(d[3]), "+f"(d[4]), "+f"(d[5]), "+f"(d[6]), "+f"(d[7]),
                   "+f"(d[8]), "+f"(d[9]), "+f"(d[10]), "+f"(d[11])
                 : "r"(a[0]), "r"(a[1]), "r"(a[2]), "r"(a[3]), "r"(lo), "r"(acc));
}
constexpr uint32_t DESC_H = 64u | (1u << 30);
constexpr uint32_t DESC_T = 256u | (1u << 30);
constexpr uint32_t DESC_G = 16u | (3u << 30);
__device__ __forceinline__ void reg_fence16(float (&d)[16]) {
    asm volatile("" : "+f"(d[0]), "+f"(d[1]), "+f"(d[2]), "+f"(d[3]), "+f"(d[4]), "+f"(d[5]), "+f"(d[6]), "+f"(d[7]),
                      "+f"(d[8]), "+f"(d[9]), "+f"(d[10]), "+f"(d[11]), "+f"(d[12]), "+f"(d[13]), "+f"(d[14]), "+f"(d[15]) :: "memory");
}
#define BLOCK_EDGE(n) asm volatile("{\n.reg .pred p;\nsetp.ge.s32 p, %0, 0;\n@p bra.uni EDGE_%=;\nnanosleep.u32 1;\nEDGE_%=:\n}\n" ::"r"(n) : "memory")
template <int V> struct IC { static constexpr int value = V; };
__device__ __forceinline__ uint32_t pin(uint32_t x) { return __shfl_sync(0xffffffffu, x, threadIdx.x & 31); }

__device__ __forceinline__ void scan1536(int* h, int pt) {
    int4* h4 = reinterpret_cast<int4*>(h) + pt * 3;
    int4 a = h4[0], b = h4[1], c = h4[2];
    a.y += a.x; a.z += a.y; a.w += a.z; b.x += a.w; b.y += b.x; b.z += b.y; b.w += b.z;
    c.x += b.w; c.y += c.x; c.z += c.y; c.w += c.z;
    int incl = c.w;
#pragma unroll
    for (int o = 1; o < 32; o <<= 1) {
        const int v = __shfl_up_sync(0xffffffffu, incl, o);
        if ((pt & 31) >= o) incl += v;
    }
    if ((pt & 31) == 31) h[1536 + (pt >> 5)] = incl;
    asm volatile("bar.sync 4, 128;" ::: "memory");
    const int ex = __reduce_add_sync(0xffffffffu, (pt & 31) < (pt >> 5) ? h[1536 + (pt & 31)] : 0) + incl - c.w;
    h4[0] = make_int4(ex, ex + a.x, ex + a.y, ex + a.z);
    h4[1] = make_int4(ex + a.w, ex + b.x, ex + b.y, ex + b.z);
    h4[2] = make_int4(ex + b.w, ex + c.x, ex + c.y, ex + c.z);
}

__device__ __forceinline__ uint32_t placed(uint32_t y) { return (y << 5) - 23u * (y & 7u); }

template <bool FITS, bool ROWS>
__device__ __forceinline__ void producer_loop(unsigned char* smem, const __nv_bfloat16* __restrict__ sv, int N, int pw) {
    const uint32_t sbase = smem_u32(smem);
    const int un = pw & 1;
    const uint32_t ubase = sbase + un * STAGES * STAGE_BYTES;
    const int* b2 = reinterpret_cast<const int*>(smem + MS_B2);
    const int ln = pin(threadIdx.x & 31);
    const int r4 = ln >> 3;
    const unsigned char* gsrc = g_tab + 2048;
    asm volatile("" : "+l"(gsrc));
    const uint32_t l7 = pin(ln & 7);
    const uint32_t d0 = r4 * 128 + (((ln & 7) ^ r4) << 4);
    const uint32_t goff = ST_G + ln * 32 + (((ln >> 2) & 1) << 4);
    const unsigned char* ghot = smem + (MS_GH - HOT0 * 32);
    const unsigned char* gcold = reinterpret_cast<const unsigned char*>(g_G);
    asm volatile("" : "+l"(ghot), "+l"(gcold));
    const int total = (int)__reduce_or_sync(0xffffffffu, (uint32_t)b2[NBIN]);
    const int half = total >> 1;
    const int ulo = un ? half : 0, uhi = un ? total : half;
    const int nnodes = min(NPC, N - (int)blockIdx.x * NPC);
    uint32_t todo;
    {
        const int beg = b2[min(ln, NQ) * NCTA], end = b2[min(ln + 1, NQ) * NCTA];
        todo = __ballot_sync(0xffffffffu, ln < NQ && (un ? (beg >= half || end > half) : beg < half));
    }
    uint32_t k = 0;
    const uint32_t kb = pw >> 1;
    do {
        const int q = todo ? __ffs(todo) - 1 : 0;
        const bool none = todo == 0;
        todo &= todo - 1;
        const int beg = (int)__reduce_or_sync(0xffffffffu, (uint32_t)b2[q * NCTA]);
        const int ge = (int)__reduce_or_sync(0xffffffffu, (uint32_t)b2[(q + 1) * NCTA]);
        const bool own = beg >= ulo && !none;
        const int lo = max(beg, ulo), hi = min(ge, uhi);
        int rem = none ? 0 : hi - lo;
        const int lastcap = own ? 24 : 32;
        const uint32_t flast = ((uint32_t)q << 8) | (none ? 0u : own ? (ge > uhi ? 18u : 2u) : 4u) | (todo ? 0u : 8u);
        bool last;
        do {
            last = rem <= lastcap;
            if ((k & 1u) == kb) {
                const uint32_t sb = ubase + (k & (STAGES - 1)) * STAGE_BYTES;
                const uint32_t bar = sbase + MS_CTL + (un * STAGES + (k & (STAGES - 1))) * 32;
                const bool valid = ln < rem;
                uint2 r = make_uint2(0, 0);
                if (!FITS) {
                    if (valid) {
                        const int j = hi - rem + ln;
                        const int* prq = b2 + q * NCTA;
                        int l0 = 0, up = NCTA;
                        while (up - l0 > 1) {
                            const int mid = (l0 + up) >> 1;
                            if (prq[mid] <= j) l0 = mid; else up = mid;
                        }
                        const int b0 = __ldcg(reinterpret_cast<const unsigned short*>(g_pfx + (l0 * NCTA + blockIdx.x) * 2) + q + (q >= 7));
                        r = __ldcg(g_rec + l0 * CH + b0 + (j - prq[l0]));
                        r.y = placed(r.y);
                    }
                } else if (!ROWS) {
                    asm volatile("ld.shared.v2.u32 {%0,%1}, [%2];" : "=r"(r.x), "=r"(r.y) : "r"(sbase + MS_REC + (hi - rem + ln) * 8));
                    if (!valid) r = make_uint2(0, 0);
                }
                if (ROWS) {
                    uint32_t sr[8];
#pragma unroll
                    for (int i = 0; i < 8; i++) {
                        if (FITS) asm volatile("ld.shared.u32 %0, [%1];" : "=r"(sr[i]) : "r"(sbase + MS_REC + 4 + (hi - rem + r4 + 4 * i) * 8));
                        else sr[i] = __shfl_sync(0xffffffffu, r.y, i * 4 + r4);
                    }
                    const int lim = rem - r4;
                    mbar_wait(bar + 24, ((k >> 2) & 1u) ^ 1u);
                    const uint32_t dpa = sb + d0, dpb = (dpa ^ 64u) + 512u;
                    const bool svl = last && own;
#pragma unroll
                    for (int i = 0; i < 8; i++) {
                        if (i < 6 || !svl) {
                            asm volatile("{\n.reg .pred p;\nsetp.le.s32 p, %2, %3;\n"
                                         "cp.async.cg.shared.global [%0], [%1+-2048], 16, p;\n"
                                         "cp.async.cg.shared.global [%0+4096], [%1+-1024], 16, p;\n"
                                         "cp.async.cg.shared.global [%0+8192], [%1], 16, p;\n"
                                         "cp.async.cg.shared.global [%0+12288], [%1+1024], 16, p;\n}\n"
                                         ::"r"(((i & 1) ? dpb : dpa) + (i >> 1) * 1024),
                                           "l"(gsrc + (size_t)((sr[i] & 0x7ffffu) ^ l7) * 16),
                                           "r"(lim), "r"(4 * i) : "memory");
                        } else {
                            asm volatile("{\n.reg .pred p;\nsetp.le.s32 p, %2, %3;\n"
                                         "cp.async.cg.shared.global [%0], [%1], 16, p;\n"
                                         "cp.async.cg.shared.global [%0+4096], [%1+128], 16, p;\n"
                                         "cp.async.cg.shared.global [%0+8192], [%1+256], 16, p;\n"
                                         "cp.async.cg.shared.global [%0+12288], [%1+384], 16, p;\n}\n"
                                         ::"r"(((i & 1) ? dpb : dpa) + (i >> 1) * 1024),
                                           "l"(reinterpret_cast<const unsigned char*>(sv) + (size_t)(blockIdx.x * NPC + q * GRP + r4 + 4 * (i - 6)) * 512 + (ln & 7) * 16),
                                           "r"(nnodes - q * GRP - r4), "r"(4 * (i - 6)) : "memory");
                        }
                    }
                    asm volatile("cp.async.mbarrier.arrive.noinc.shared::cta.b64 [%0];" ::"r"(bar) : "memory");
                } else {
                    const uint32_t rxy = hmul2(r.x & 0x9fff9fffu, 0x60806080u);
                    const uint32_t rz2 = hmul2((r.y >> 19) | ((r.x >> 15) & 0x8000u), 0x60806080u);
                    const uint32_t qxy = hmul2(rxy, rxy), qz = hmul2(rz2, rz2);
                    const float sum = bf16r((__uint_as_float(qxy << 16) + __uint_as_float(qxy & 0xffff0000u)) + __uint_as_float(qz << 16));
                    float sq;
                    asm("sqrt.approx.ftz.f32 %0, %1;" : "=f"(sq) : "f"(bf16r(sum + 1e-8f)));
                    const uint32_t dbits = pack_bf16(0.f, sq);
                    float rinv;
                    asm("rcp.approx.ftz.f32 %0, %1;" : "=f"(rinv) : "f"(__uint_as_float(dbits)));
                    const int di = valid ? max(min((int)(dbits >> 16), DEND - 1) - DBASE, 0) : NTAB - 1;
                    const uint4* gp = reinterpret_cast<const uint4*>(di >= HOT0 ? ghot : gcold) + 2 * di;
                    const uint4 g0 = gp[0], g1 = gp[1];
                    const uint32_t r01 = pack_bf16(__uint_as_float(rxy << 16) * rinv, __uint_as_float(rxy & 0xffff0000u) * rinv);
                    const bool self = last && own && ln >= 24;
                    const uint32_t r2 = pack_bf16(__uint_as_float(rz2 << 16) * rinv, (valid || self) ? 1.0f : 0.f);
                    const uint32_t so = self ? (ln & 7) * 2 : ((r.x >> 12) & 6u) | ((r.x >> 26) & 8u);
                    mbar_wait(bar + 8, ((k >> 2) & 1u) ^ 1u);
                    const uint32_t za = sb + ST_S + ln * 16;
#pragma unroll
                    for (int j = 0; j < 4; j++)
                        asm volatile("st.shared.v4.u32 [%0], {%1,%1,%1,%1};" ::"r"(za + j * 512), "r"(0u) : "memory");
                    asm volatile("st.shared.u16 [%0], %1;" ::"r"(za + so), "h"((unsigned short)(r2 >> 16)) : "memory");
                    asm volatile("st.shared.u16 [%0+512], %1;" ::"r"(za + so), "h"((unsigned short)(r01 & 0xffffu)) : "memory");
                    asm volatile("st.shared.u16 [%0+1024], %1;" ::"r"(za + so), "h"((unsigned short)(r01 >> 16)) : "memory");
                    asm volatile("st.shared.u16 [%0+1536], %1;" ::"r"(za + so), "h"((unsigned short)(r2 & 0xffffu)) : "memory");
                    asm volatile("st.shared.u32 [%0+16], %1;" ::"r"(bar), "r"(last ? flast : 0u) : "memory");
                    asm volatile("st.shared.v4.u32 [%0], {%1,%2,%3,%4};" ::"r"(sb + goff),
                                 "r"(g0.x), "r"(g0.y), "r"(g0.z), "r"(g0.w) : "memory");
                    asm volatile("st.shared.v4.u32 [%0], {%1,%2,%3,%4};" ::"r"((sb + goff) ^ 16u),
                                 "r"(g1.x), "r"(g1.y), "r"(g1.z), "r"(g1.w) : "memory");
                    asm volatile("fence.proxy.async.shared::cta;" ::: "memory");
                    mbar_arrive(bar);
                }
            }
            k++;
            rem -= 32;
        } while (!last);
    } while (todo);
    if ((k & 1u) == kb) {
        const uint32_t bar = sbase + MS_CTL + (un * STAGES + (k & (STAGES - 1))) * 32;
        mbar_wait(bar + 8, ((k >> 2) & 1u) ^ 1u);
        mbar_arrive(bar);
    }
}

__global__ void __launch_bounds__(M_THREADS, 1)
fused_kernel(const __nv_bfloat16* __restrict__ sv, const __nv_bfloat16* __restrict__ pos,
             const int* __restrict__ src, const int* __restrict__ dst,
             const __nv_bfloat16* __restrict__ freqs, const __nv_bfloat16* __restrict__ w1,
             const __nv_bfloat16* __restrict__ w2, const __nv_bfloat16* __restrict__ wrbf,
             __nv_bfloat16* __restrict__ out, int N, int E) {
    extern __shared__ __align__(1024) unsigned char smem[];
    const uint32_t swz = (threadIdx.x >> 3) * 128 + (((threadIdx.x ^ (threadIdx.x >> 3)) & 7) << 4);
    const uint32_t tl0 = smem_u32(smem) + PS_TILE + swz + (threadIdx.x >> 6) * (4096 - 1024);
    const __nv_bfloat16* sv0 = sv + (size_t)min((int)(blockIdx.x * TPC + (threadIdx.x >> 3)), N - 1) * 256 + (threadIdx.x & 7) * 8;
    const __nv_bfloat16* sv1 = sv + (size_t)min((int)(blockIdx.x * TPC + 64 + (threadIdx.x >> 3)), N - 1) * 256 + (threadIdx.x & 7) * 8;
    cp_async16(tl0, sv0);
    cp_async16(smem_u32(smem) + PS_W1 + swz, w1 + threadIdx.x * 8);
    cp_async16(smem_u32(smem) + PS_W1 + 8192 + swz, w2 + (threadIdx.x >> 3) * 192 + 64 + (threadIdx.x & 7) * 8);
    if (threadIdx.x < 128) cp_async16(tl0 + 32768, sv1);
    unsigned short freq_bits;
    asm volatile("ld.global.nc.u16 %0, [%1];" : "=h"(freq_bits) : "l"(freqs + (threadIdx.x & 15)));
    if (threadIdx.x == 480) {
        const uint32_t sb0 = smem_u32(smem);
        const int n4 = max(min(EPC, E - (int)blockIdx.x * EPC), 0) * 4;
        mbar_init(sb0 + MS_BAR, 1);
        asm volatile("fence.mbarrier_init.release.cluster;" ::: "memory");
        mbar_expect_tx(sb0 + MS_BAR, N * 6 + n4 * 2);
        if (n4 > 0) {
            bulk_g2s(sb0 + PS_SRC, src + blockIdx.x * EPC, n4, sb0 + MS_BAR);
            bulk_g2s(sb0 + PS_DST, dst + blockIdx.x * EPC, n4, sb0 + MS_BAR);
        }
        bulk_g2s(sb0 + PS_POS, pos, N * 6, sb0 + MS_BAR);
    }
    __syncwarp();
    const int tid = threadIdx.x, lane = tid & 31;
    const int warp = (int)__reduce_or_sync(0xffffffffu, (uint32_t)tid >> 5);
    const uint32_t sbase = smem_u32(smem);
    const uint32_t ghbar = sbase + MS_BAR;
    const int cta = blockIdx.x;
    const int nnodes = min(NPC, N - cta * NPC);

    STAMP(0, 0);
    int* hist = reinterpret_cast<int*>(smem + PS_HIST);
    int* b2 = reinterpret_cast<int*>(smem + MS_B2);
    const int ne = max(min(EPC, E - cta * EPC), 0);
    const uint32_t fo = ((lane & 7) + 8 * (lane >> 4)) * 128 + ((uint32_t)((2 * (warp & 3) + ((lane >> 3) & 1)) ^ (lane & 7)) << 4);
    const uint32_t tb = sbase + PS_TILE + (warp >> 2) * 16384;
    const bool tstore = warp < TPC / 8 && cta * TPC + warp * 8 < N;
    unsigned char* tdst = g_tab + (size_t)(cta * (TPC / 8) + warp) * 4096;
    const uint32_t tsrc = sbase + PS_TILE + warp * 4096;
    const uint32_t ta = tb + fo + (lane >> 4) * (4096 - 1024);
    STAMP(16, 480);
    unsigned int epoch;
    uint32_t x[2][4];
    if (warp < 12) {
        reinterpret_cast<int4*>(hist)[tid] = make_int4(0, 0, 0, 0);
        asm volatile("bar.arrive 2, 512;" ::: "memory");
        asm volatile("cp.async.wait_all;" ::: "memory");
        asm volatile("fence.proxy.async.shared::cta;" ::: "memory");
        asm volatile("bar.sync 3, 512;" ::: "memory");
        STAMP(12, 0);
        const uint32_t dh = (tb >> 4) | (1u << 16);
#pragma unroll 1
        for (int it = 0; it < 2; it++) {
            uint32_t a[4][4];
            float d[16] = {};
#pragma unroll
            for (int q = 0; q < 4; q++) ldsm4t(a[q], sbase + PS_W1 + it * 8192 + q * 2048 + fo);
            asm volatile("wgmma.fence.sync.aligned;" ::: "memory");
            wgmma_n32<0, DESC_T>(d, a[0], dh);
            wgmma_n32<1, DESC_T>(d, a[1], dh + 2);
            wgmma_n32<1, DESC_T>(d, a[2], dh + 4);
            wgmma_n32<1, DESC_T>(d, a[3], dh + 6);
            asm volatile("wgmma.commit_group.sync.aligned;" ::: "memory");
            asm volatile("wgmma.wait_group.sync.aligned 0;" ::: "memory");
            reg_fence16(d);
#pragma unroll
            for (int i = 0; i < 8; i++) x[i >> 2][i & 3] = pack_bf16(d[2 * i], d[2 * i + 1]);
            if (it) break;
#pragma unroll
            for (int i = 0; i < 8; i++) {
                const float z0 = __uint_as_float(x[i >> 2][i & 3] << 16), z1 = __uint_as_float(x[i >> 2][i & 3] & 0xffff0000u);
                float e0, e1;
                asm("ex2.approx.ftz.f32 %0, %1;" : "=f"(e0) : "f"(z0 * -1.4426950408889634f));
                asm("ex2.approx.ftz.f32 %0, %1;" : "=f"(e1) : "f"(z1 * -1.4426950408889634f));
                asm("rcp.approx.ftz.f32 %0, %1;" : "=f"(e0) : "f"(e0 + 1.0f));
                asm("rcp.approx.ftz.f32 %0, %1;" : "=f"(e1) : "f"(e1 + 1.0f));
                x[i >> 2][i & 3] = pack_bf16(z0 * e0, z1 * e1);
            }
            asm volatile("bar.sync %0, 128;" ::"r"(5 + (warp >> 2)) : "memory");
            stsm4t(ta, x[0]);
            stsm4t(ta + 8192, x[1]);
            asm volatile("fence.proxy.async.shared::cta;" ::: "memory");
            asm volatile("bar.sync %0, 128;" ::"r"(5 + (warp >> 2)) : "memory");
            if (tstore && lane == 0) bulk_s2g(tdst, tsrc, 1024);
        }
        STAMP(13, 0);
    } else {
        const int pt = tid - 384;
        asm volatile("cp.async.wait_all;" ::: "memory");
        asm volatile("fence.proxy.async.shared::cta;" ::: "memory");
        asm volatile("bar.arrive 3, 512;" ::: "memory");
#pragma unroll
        for (int i = pt; i < 2 * NCTA; i += 128)
            asm volatile("st.relaxed.gpu.global.v4.u32 [%0], {%1,%1,%1,%1};" ::"l"(g_pfx + cta * NCTA * 2 + i), "r"(0) : "memory");
#pragma unroll 1
        for (int gi = cta * 256 + pt; gi < min(cta * 256 + 256, NTAB * NRBF); gi += 128) {
            const float d = __uint_as_float((uint32_t)(DBASE + (gi >> 4)) << 16);
            const float arg = bf16r(d * __uint_as_float((uint32_t)freq_bits << 16));
            float sn;
            if (fabsf(arg) < 1000.f) {
                const float k = rintf(arg * 0.15915494309189535f);
                sn = __sinf(fmaf(k, 1.7484556000744883e-7f, fmaf(k, -6.2831854820251465f, arg)));
            } else {
                sn = sinf(arg);
            }
            const float rbf = bf16r(__fdividef(bf16r(sn), d));
            const float ca = bf16r(bf16r(3.14159265358979f * d) * 0.2f);
            const float fc = 0.5f * bf16r(bf16r(__cosf(ca)) + 1.0f);
            g_G[gi] = __float2bfloat16_rn(rbf * fc);
        }
        STAMP(17, 384);
        asm volatile("bar.sync 2, 512;" ::: "memory");
    }
    mbar_wait(ghbar, 0);
    STAMP(1, 0);
#pragma unroll
    for (int c = 1; c < 4; c++) cp_async16(tl0 + c * 1024, sv0 + c * 64);
    if (warp < 4) {
#pragma unroll
        for (int c = 1; c < 4; c++) cp_async16(tl0 + 32768 + c * 1024, sv1 + c * 64);
    } else if (warp >= 12) {
        const int pt = tid - 384;
#pragma unroll
        for (int k = 0; k < 4; k++) {
            const int r = (pt >> 3) + 16 * k, c = pt & 7;
            cp_async16(sbase + PS_W2 + r * 272 + c * 16, w2 + r * 192 + c * 8);
            cp_async16(sbase + PS_W2 + r * 272 + 128 + c * 16, w2 + r * 192 + 128 + c * 8);
            if (k < 3) cp_async16(sbase + PS_WR + (pt >> 3) * 400 + k * 128 + c * 16, wrbf + (pt >> 3) * 192 + k * 64 + c * 8);
        }
    }
    asm volatile("ld.relaxed.gpu.global.u32 %0, [%1];" : "=r"(epoch) : "l"(&g_cnt));
    {
        uint32_t pb = sbase + PS_POS;
        asm volatile("" : "+r"(pb) :: "memory");
        uint32_t es[10], ed[10], key[10];
#pragma unroll
        for (int k = 0; k < 2; k++) {
            const uint4 a = reinterpret_cast<const uint4*>(smem + PS_SRC)[tid + k * 512];
            const uint4 b = reinterpret_cast<const uint4*>(smem + PS_DST)[tid + k * 512];
            es[4 * k] = a.x; es[4 * k + 1] = a.y; es[4 * k + 2] = a.z; es[4 * k + 3] = a.w;
            ed[4 * k] = b.x; ed[4 * k + 1] = b.y; ed[4 * k + 2] = b.z; ed[4 * k + 3] = b.w;
        }
        {
            const uint2 a = reinterpret_cast<const uint2*>(smem + PS_SRC)[2048 + tid];
            const uint2 b = reinterpret_cast<const uint2*>(smem + PS_DST)[2048 + tid];
            es[8] = a.x; es[9] = a.y; ed[8] = b.x; ed[9] = b.y;
        }
#pragma unroll
        for (int e = 0; e < 10; e++) {
            const bool ok = (e < 8 ? 4 * (tid + (e >> 2) * 512) : 4096 + 2 * tid) < ne;
            const uint32_t sn = ok ? es[e] : 0u, dn = ok ? ed[e] : 0u;
            const uint32_t as = pb + sn * 6, ad = pb + dn * 6;
            uint32_t sa, sb, da, db;
            asm("ld.shared.u32 %0, [%2];\nld.shared.u32 %1, [%2+4];" : "=r"(sa), "=r"(sb) : "r"(as & ~3u));
            asm("ld.shared.u32 %0, [%2];\nld.shared.u32 %1, [%2+4];" : "=r"(da), "=r"(db) : "r"(ad & ~3u));
            const uint32_t rxy = hsub2(__funnelshift_r(sa, sb, as << 3), __funnelshift_r(da, db, ad << 3));
            const uint32_t rz = hsub2(__funnelshift_r(sb, 0u, as << 3), __funnelshift_r(db, 0u, ad << 3));
            const uint32_t qxy = hmul2(rxy, rxy), qz = hmul2(rz, rz);
            const float sum = (__uint_as_float(qxy << 16) + __uint_as_float(qxy & 0xffff0000u)) + __uint_as_float(qz << 16);
            const uint32_t c = dn / NPC, dl = dn - c * NPC, q = dl >> 3;
            const uint32_t ez = hmul2(rz, 0x1e801e80u);
            es[e] = (ez & 0x1fffu) * 0x4000u + sn + q * 0x10000000u;
            ed[e] = hmul2(rxy, 0x1e801e80u) | ((dl * 0x08002000u) & 0x20006000u) | ((ez << 15) & 0x40000000u);
            key[e] = sbase + PS_HIST + ((sum < 23.9375f && ok) ? c * NQ + q : 1504 + lane) * 4;
        }
#pragma unroll
        for (int e = 0; e < 10; e++) {
            uint32_t rank;
            asm volatile("atom.shared.add.u32 %0, [%1], 1;" : "=r"(rank) : "r"(key[e]) : "memory");
            key[e] = (key[e] << 13) | rank;
        }
        STAMP(18, 0);
        asm volatile("cp.async.wait_all;" ::: "memory");
        __syncthreads();
        STAMP(14, 0);
        if (warp >= 12) {
            scan1536(hist, tid - 384);
        } else {
            uint32_t v[6][4];
#pragma unroll
            for (int j = 0; j < 6; j++) ldsm4t(v[j], ta + 1024 + (j >> 1) * 1024 + (j & 1) * 8192);
#pragma unroll
            for (int j = 0; j < 6; j++) {
#pragma unroll
                for (int e = 0; e < 4; e++) v[j][e] = hmul2(v[j][e], x[j & 1][e]);
                stsm4t(ta + 1024 + (j >> 1) * 1024 + (j & 1) * 8192, v[j]);
            }
            asm volatile("fence.proxy.async.shared::cta;" ::: "memory");
            STAMP(15, 0);
        }
        __syncthreads();
        if (tstore && lane == 0) bulk_s2g(tdst + 1024, tsrc + 1024, 3072);
        STAMP(3, 0);
        const int nact = hist[NBIN];
        int o[10];
#pragma unroll
        for (int e = 0; e < 10; e++) asm volatile("ld.shared.u32 %0, [%1];" : "=r"(o[e]) : "r"(key[e] >> 13));
#pragma unroll
        for (int e = 0; e < 10; e++) {
            o[e] += key[e] & 8191;
            asm volatile("{\n.reg .pred p;\nsetp.lt.s32 p, %0, %1;\n@p st.shared.v2.u32 [%2], {%3, %4};\n}\n"
                         ::"r"(o[e]), "r"(nact), "r"(sbase + PS_POS + o[e] * 8), "r"(ed[e]), "r"(es[e]) : "memory");
        }
        asm volatile("fence.proxy.async.shared::cta;" ::: "memory");
        __syncthreads();
        STAMP(4, 0);
        if (tid == 480 && nact > 0) bulk_s2g(g_rec + cta * CH, sbase + PS_POS, ((nact + 1) >> 1) * 16);
        asm volatile("cp.async.bulk.commit_group;" ::: "memory");
    }
    const uint32_t tag = (epoch / NCTA + 1) << 16;
    uint4 pv;
    {
        const int i = min(tid, 2 * NCTA - 1);
        const int* h = hist + (i >> 1) * NQ + (i & 1) * 7;
        pv = make_uint4(h[0] | (h[1] << 16), h[2] | (h[3] << 16), h[4] | (h[5] << 16), h[6] | tag);
    }
    asm volatile("cp.async.bulk.wait_group 0;" ::: "memory");
    __syncthreads();
    STAMP(2, 0);
    if (warp == 15) {
        asm volatile("fence.acq_rel.gpu;" ::: "memory");
    } else if (warp < UNITS * STAGES) {
        if (lane == 0) {
            mbar_init(sbase + MS_CTL + warp * 32, 64);
            mbar_init(sbase + MS_CTL + warp * 32 + 8, 4);
            mbar_init(sbase + MS_CTL + warp * 32 + 24, 4);
        }
    } else if (warp == 8) {
        if (lane == 0) mbar_init(ghbar + 8, 128);
        reinterpret_cast<int*>(smem + MS_MISC)[lane] = 0;
    } else if (tid - 288 < (1536 - NBIN) / 4) {
        reinterpret_cast<int4*>(b2 + NBIN)[tid - 288] = make_int4(0, 0, 0, 0);
    }
    __syncthreads();
    if (warp < 9)
        asm volatile("st.relaxed.gpu.global.v4.u32 [%0], {%1,%2,%3,%4};" ::"l"(g_pfx + cta * NCTA * 2 + min(tid, 2 * NCTA - 1)),
                     "r"(pv.x), "r"(pv.y), "r"(pv.z), "r"(pv.w) : "memory");
    STAMP(6, 0);
    if (warp == 15) {
        if (lane == 0) atomicInc(&g_cnt, NCTA * 65535u - 1);
    } else {
        unsigned short* pf = reinterpret_cast<unsigned short*>(smem + PS_PF);
        const int p0 = 9 * warp;
        const int p = min(p0 + min(lane >> 1, 8), NCTA - 1);
        uint4 v = make_uint4(0, 0, 0, lane < 18 ? ~tag : tag);
        int spin = 0;
        do {
            asm volatile("{\n.reg .pred p;\nsetp.ne.u32 p, %5, 0;\n@p ld.acquire.gpu.global.v4.u32 {%0,%1,%2,%3}, [%4];\n}\n"
                         : "+r"(v.x), "+r"(v.y), "+r"(v.z), "+r"(v.w)
                         : "l"(g_pfx + (p * NCTA + cta) * 2 + (lane & 1)), "r"((v.w ^ tag) & 0xffff0000u) : "memory");
        } while (__any_sync(0xffffffffu, (v.w ^ tag) & 0xffff0000u) && ++spin < (1 << 22));
        STAMP(7, 0);
        if (lane < 18) reinterpret_cast<uint4*>(pf)[p * 2 + (lane & 1)] = v;
        uint32_t be = __byte_perm(v.x, __shfl_down_sync(0xffffffffu, v.y, 1), 0x7610);
        if (lane >= 18 || p0 + (lane >> 1) >= NCTA) be = 0;
        const int hw = lane >> 4;
        const uint4* gr = reinterpret_cast<const uint4*>(g_rec + (p0 + hw) * CH) + (lane & 15);
        uint4 r[5], r2[5];
        uint32_t sg[5];
        bool more = false;
#pragma unroll
        for (int k = 0; k < 5; k++) {
            sg[k] = __shfl_sync(0xffffffffu, be, 4 * k + 2 * hw);
            const int ib = (sg[k] & 0xffffu) >> 1, ie = (sg[k] >> 16) - 2 * (lane & 15);
            if (2 * ib < ie) r[k] = __ldcg(gr + k * CH + ib);
            if (2 * ib + 32 < ie) { r2[k] = __ldcg(gr + k * CH + ib + 16); more = true; }
        }
        __syncwarp();
        int* gcnt = reinterpret_cast<int*>(smem + MS_MISC) + 8;
        int* dl = reinterpret_cast<int*>(smem + PS_DL);
        int rel[3];
#pragma unroll
        for (int j = 0; j < 3; j++) {
            const int e = lane + 32 * j, k = e / NQ, q = e - k * NQ, pp = p0 + k;
            if (k < 9 && pp < NCTA) {
                const int lo = pf[pp * 16 + q + (q >= 7)];
                const int c = pf[pp * 16 + q + 1 + (q >= 6)] - lo;
                b2[q * NCTA + pp] = c;
                rel[j] = atomicAdd(&gcnt[q], c) - lo;
            }
        }
        asm volatile("bar.sync 1, 480;" ::: "memory");
        STAMP(9, 0);
#pragma unroll
        for (int i = tid; i < (NTAB - HOT0) * 2; i += 480) cp_async16(sbase + MS_GH + i * 16, g_G + HOT0 * NRBF + i * 8);
        int gb = lane < NQ ? gcnt[lane] : 0;
        const int own = gb;
#pragma unroll
        for (int o = 1; o < 16; o <<= 1) {
            const int y = __shfl_up_sync(0xffffffffu, gb, o);
            if (lane >= o) gb += y;
        }
        gb -= own;
        if (__shfl_sync(0xffffffffu, gb, NQ) > RCAP) {
            if (warp < 4) scan1536(b2, tid);
        } else {
#pragma unroll
            for (int j = 0; j < 3; j++) {
                const int e = lane + 32 * j, k = e / NQ, q = e - k * NQ, pp = p0 + k;
                const int g0 = __shfl_sync(0xffffffffu, gb, q);
                if (k < 9 && pp < NCTA) dl[q * NCTA + pp] = rel[j] + g0;
            }
            if (warp == 0 && lane <= NQ) b2[lane * NCTA] = gb;
            __syncwarp();
            STAMP(11, 0);
            const uint32_t da = sbase + PS_DL + (p0 + hw) * 4;
            auto place = [&](const uint4& x, int k, int off) {
                const int beg = sg[k] & 0xffffu, end = sg[k] >> 16, i = (beg & ~1) + 2 * (lane & 15) + off;
                asm volatile("{\n.reg .pred p, q;\n.reg .b32 a, b;\n"
                             "setp.lt.s32 q, %8, %2;\nsetp.ge.and.s32 p, %0, %1, q;\nsetp.lt.s32 q, %0, %9;\n"
                             "@p ld.shared.u32 a, [%3];\n@q ld.shared.u32 b, [%4];\n"
                             "add.s32 a, a, %0;\nadd.s32 b, b, %0;\nmad.lo.s32 a, a, 8, %5;\nmad.lo.s32 b, b, 8, %5;\n"
                             "@p st.shared.v2.u32 [a], {%6, %7};\n@q st.shared.v2.u32 [b+8], {%10, %11};\n}\n"
                             ::"r"(i), "r"(beg), "r"(end), "r"(da + k * 8 + (x.y >> 28) * (NCTA * 4)), "r"(da + k * 8 + (x.w >> 28) * (NCTA * 4)),
                               "r"(sbase + MS_REC), "r"(x.x), "r"(placed(x.y)), "r"(i), "r"(end - 1), "r"(x.z), "r"(placed(x.w)) : "memory");
            };
#pragma unroll
            for (int k = 0; k < 5; k++) place(r[k], k, 0);
            if (__any_sync(0xffffffffu, more)) {
                bool rest = false;
#pragma unroll
                for (int k = 0; k < 5; k++) {
                    place(r2[k], k, 32);
                    rest |= (sg[k] & 0xfffeu) + 64 < (sg[k] >> 16);
                }
                if (__any_sync(0xffffffffu, rest)) {
#pragma unroll 1
                    for (int pp = p0; pp < min(p0 + 9, NCTA); pp++) {
#pragma unroll 1
                        for (int i = (pf[pp * 16] & ~1) + 64 + lane; i < pf[pp * 16 + NQ + 1]; i += 32) {
                            const uint2 x = __ldcg(g_rec + pp * CH + i);
                            reinterpret_cast<uint2*>(smem + MS_REC)[reinterpret_cast<const int*>(smem + PS_DL)[(x.y >> 28) * NCTA + pp] + i] =
                                make_uint2(x.x, placed(x.y));
                        }
                    }
                }
            }
        }
        asm volatile("cp.async.wait_all;" ::: "memory");
    }
    __syncthreads();
    STAMP(10, 0);

    if (warp >= 12) {
        asm volatile("setmaxnreg.dec.sync.aligned.u32 32;");
        STAMP(21, 384);
        if (__reduce_or_sync(0xffffffffu, (uint32_t)b2[NBIN]) <= RCAP) producer_loop<true, true>(smem, sv, N, warp - 12);
        else producer_loop<false, true>(smem, sv, N, warp - 12);
        GSTAMP(22 + (warp & 1), 384 + 32 * (warp & 1));
    } else if (warp >= 8) {
        asm volatile("setmaxnreg.dec.sync.aligned.u32 32;");
        if (__reduce_or_sync(0xffffffffu, (uint32_t)b2[NBIN]) <= RCAP) producer_loop<true, false>(smem, sv, N, warp - 8);
        else producer_loop<false, false>(smem, sv, N, warp - 8);
    } else {
        asm volatile("setmaxnreg.inc.sync.aligned.u32 224;");
        const int unit = warp >> 2, w = warp & 3;
        uint32_t wa[3][4], pa[2][4][4];
        {
            const int krow = (lane & 7) + 8 * (lane >> 4), mcol = 2 * w + ((lane >> 3) & 1);
#pragma unroll
            for (int q = 0; q < 4; q++) {
                ldsm4t(pa[0][q], sbase + PS_W2 + (16 * q + krow) * 272 + mcol * 16);
                ldsm4t(pa[1][q], sbase + PS_W2 + (16 * q + krow) * 272 + 128 + mcol * 16);
            }
#pragma unroll
            for (int p = 0; p < 3; p++) ldsm4t(wa[p], sbase + PS_WR + krow * 400 + p * 128 + mcol * 16);
            asm volatile("bar.sync 8, 256;" ::: "memory");
        }
        float acc[4][4], accr[12];
#pragma unroll
        for (int i = 0; i < 16; i++) acc[i >> 2][i & 3] = 0.f;
#pragma unroll
        for (int i = 0; i < 12; i++) accr[i] = 0.f;
        const uint32_t ua = pin(4096 + ((lane & 7) + 8 * (lane >> 4)) * 128 + ((uint32_t)((2 * w + ((lane >> 3) & 1)) ^ (lane & 7)) << 4));
        const uint32_t ub = sbase + unit * STAGES * STAGE_BYTES;
        const uint32_t uc = sbase + MS_CTL + unit * STAGES * 32;
        float pr[16] = {}, fr[16] = {}, fv[16] = {}, ps[16] = {}, fs[16] = {};
        auto issue = [&](uint32_t sn) {
            const uint32_t dh = (sn >> 4) | (1u << 16);
            const uint32_t dg = dh + (ST_G >> 4);
            wgmma_n32<0, DESC_H>(pr, pa[1][0], dh);
            wgmma_n32<0, DESC_H>(ps, pa[0][0], dh);
            wgmma_n32<1, DESC_H>(pr, pa[1][1], dh + 2);
            wgmma_n32<1, DESC_H>(ps, pa[0][1], dh + 2);
            wgmma_n32<1, DESC_H>(pr, pa[1][2], dh + 4);
            wgmma_n32<1, DESC_H>(ps, pa[0][2], dh + 4);
            wgmma_n32<1, DESC_H>(pr, pa[1][3], dh + 6);
            wgmma_n32<1, DESC_H>(ps, pa[0][3], dh + 6);
            wgmma_n32<0, DESC_G>(fr, wa[2], dg);
            wgmma_n32<0, DESC_G>(fv, wa[1], dg);
            wgmma_n32<0, DESC_G>(fs, wa[0], dg);
            asm volatile("wgmma.commit_group.sync.aligned;" ::: "memory");
        };
        mbar_wait(uc, 0);
        uint32_t fnext;
        asm volatile("ld.shared.u32 %0, [%1+16];" : "=r"(fnext) : "r"(uc));
        asm volatile("wgmma.fence.sync.aligned;" ::: "memory");
        issue(ub);
        uint32_t ph = 0;
        uint32_t keep = 0;
        const uint32_t lnz = pin(lane);
        const uint32_t ea = pin((lane >> 4) * 4096 + (24 + (lane & 7)) * 128 + ((uint32_t)((2 * w + ((lane >> 3) & 1)) ^ (lane & 7)) << 4));
        const uint32_t ia = pin(((lane >> 1) & 1) * 4096 + (24 + (lane >> 2)) * 128 + ((uint32_t)((2 * w + (lane & 1)) ^ (lane >> 2)) << 4));
        const unsigned char* outp = reinterpret_cast<const unsigned char*>(out) + (size_t)(blockIdx.x * NPC + (lane >> 2)) * 512 +
                                    ((lane >> 1) & 1) * 128 + (2 * w + (lane & 1)) * 16;
        const int olim = min(NPC, N - (int)blockIdx.x * NPC) - (lane >> 2);
        auto stage = [&](auto stc) -> bool {
            constexpr int st = decltype(stc)::value;
            const uint32_t sb = ub + st * STAGE_BYTES, cb = uc + st * 32;
            const uint32_t sn = ub + ((st + 1) % STAGES) * STAGE_BYTES, cn = uc + ((st + 1) % STAGES) * 32;
            if (st == STAGES - 1) ph ^= 1u;
            uint32_t ms[2][4], mr[2][4], u[2][3][4], sx[2], ready;
            const uint32_t flags = fnext;
            asm volatile("{\n.reg .pred p;\nmbarrier.test_wait.parity.shared::cta.b64 p, [%1], %2;\nselp.u32 %0, 1, 0, p;\n}\n"
                         : "=r"(ready) : "r"(cn), "r"(ph) : "memory");
#pragma unroll
            for (int j = 0; j < 3; j++) {
                ldsm4t(u[0][j], sb + ua + j * 4096);
                ldsm4t(u[1][j], sb + ua + j * 4096 + 2048);
            }
            asm volatile("ldmatrix.sync.aligned.m8n8.x2.trans.shared.b16 {%0,%1}, [%2];" : "=r"(sx[0]), "=r"(sx[1]) : "r"(sb + ua - 1024));
            asm volatile("wgmma.wait_group.sync.aligned 0;" ::: "memory");
            reg_fence16(pr); reg_fence16(fr); reg_fence16(fv); reg_fence16(ps); reg_fence16(fs);
#pragma unroll
            for (int i = 0; i < 8; i++) {
                mr[i >> 2][i & 3] = pack_bf16(fr[2 * i] * pr[2 * i], fr[2 * i + 1] * pr[2 * i + 1]);
                ms[i >> 2][i & 3] = pack_bf16(fs[2 * i] * ps[2 * i], fs[2 * i + 1] * ps[2 * i + 1]);
                uint32_t wv = pack_bf16(fv[2 * i], fv[2 * i + 1]);
                if (i >= 6 && (flags & 2u)) {
                    wv = 0x3f803f80u;
                    ms[1][i & 3] = sx[i & 1];
                }
#pragma unroll
                for (int j = 0; j < 3; j++) u[i >> 2][j][i & 3] = hmul2(u[i >> 2][j][i & 3], wv);
            }
            asm volatile("{\n.reg .pred p;\nsetp.eq.u32 p, %1, 0;\n@p mbarrier.arrive.shared::cta.b64 _, [%0];\n}\n"
                         ::"r"(cb + 24), "r"(lnz | (flags & 2u)) : "memory");
            const uint32_t ds = ((sb + ST_S) >> 4) | (8u << 16);
            if (!ready) mbar_wait(cn, ph);
            asm volatile("ld.shared.u32 %0, [%1+16];" : "=r"(fnext) : "r"(cn));
            asm volatile("wgmma.fence.sync.aligned;" ::: "memory");
#pragma unroll
            for (int s = 0; s < 2; s++) {
                wgmma_n24t(accr, mr[s], ds + 32 + 16 * s, s ? 1u : keep);
                wgmma_n8t(acc[0], ms[s], ds + 16 * s, s ? 1u : keep);
#pragma unroll
                for (int j = 0; j < 3; j++) wgmma_n8t(acc[j + 1], u[s][j], ds + 16 * s, s ? 1u : keep);
            }
            asm volatile("wgmma.commit_group.sync.aligned;" ::: "memory");
            issue(sn);
            asm volatile("wgmma.wait_group.sync.aligned 1;" ::: "memory");
            asm volatile("" : "+f"(acc[0][0]), "+f"(acc[0][1]), "+f"(acc[0][2]), "+f"(acc[0][3]), "+f"(acc[1][0]), "+f"(acc[1][1]),
                              "+f"(acc[1][2]), "+f"(acc[1][3]), "+f"(acc[2][0]), "+f"(acc[2][1]), "+f"(acc[2][2]), "+f"(acc[2][3]),
                              "+f"(acc[3][0]), "+f"(acc[3][1]), "+f"(acc[3][2]), "+f"(acc[3][3]) :: "memory");
            asm volatile("" : "+f"(accr[0]), "+f"(accr[1]), "+f"(accr[2]), "+f"(accr[3]), "+f"(accr[4]), "+f"(accr[5]),
                              "+f"(accr[6]), "+f"(accr[7]), "+f"(accr[8]), "+f"(accr[9]), "+f"(accr[10]), "+f"(accr[11]) :: "memory");
            asm volatile("{\n.reg .pred p;\nsetp.eq.u32 p, %1, 0;\n@p mbarrier.arrive.shared::cta.b64 _, [%0];\n}\n"
                         ::"r"(cb + 8), "r"(lnz) : "memory");
            keep = flags == 0;
            if (flags) {
                float o[16];
#pragma unroll
                for (int i = 0; i < 16; i++) o[i] = i < 4 ? acc[0][i] : acc[i >> 2][i & 3] + accr[i - 4];
                if (flags & 20u) {
                    float* part = reinterpret_cast<float*>(smem + MS_PART) + (tid & 127);
                    if (flags & 4u) {
#pragma unroll
                        for (int i = 0; i < 16; i++) part[i * 128] = o[i];
                        mbar_arrive(sbase + MS_BAR + 8);
                    } else {
                        mbar_wait_ft(sbase + MS_BAR + 8, 0);
#pragma unroll
                        for (int i = 0; i < 16; i++) o[i] += part[i * 128];
                    }
                }
                if (flags & 2u) {
#pragma unroll
                    for (int kk = 0; kk < 2; kk++) {
                        uint32_t v[4];
#pragma unroll
                        for (int e = 0; e < 4; e++) v[e] = pack_bf16(o[8 * kk + 2 * e], o[8 * kk + 2 * e + 1]);
                        stsm4t(sb + ea + kk * 8192, v);
                    }
                    __syncwarp();
                    const unsigned char* op = outp + (size_t)(flags >> 8) * (GRP * 512);
#pragma unroll
                    for (int kk = 0; kk < 2; kk++) {
                        asm volatile("{\n.reg .pred p;\n.reg .b32 a, b, c, d;\nsetp.lt.s32 p, %2, %3;\n"
                                     "ld.shared.v4.u32 {a, b, c, d}, [%0];\n"
                                     "@p st.global.v4.u32 [%1], {a, b, c, d};\n}\n"
                                     ::"r"(sb + ia + kk * 8192), "l"(op + kk * 256), "r"((int)(flags >> 8) * GRP), "r"(olim) : "memory");
                    }
                    __syncwarp();
                    asm volatile("{\n.reg .pred p;\nsetp.eq.u32 p, %1, 0;\n@p mbarrier.arrive.shared::cta.b64 _, [%0];\n}\n"
                                 ::"r"(cb + 24), "r"(lnz) : "memory");
                }
                if (flags & 8u) return true;
            }
            return false;
        };
        while (true) {
            if (stage(IC<0>{})) break;
            if (stage(IC<1>{})) break;
            if (stage(IC<2>{})) break;
            if (stage(IC<3>{})) break;
        }
        asm volatile("wgmma.wait_group.sync.aligned 0;" ::: "memory");
        GSTAMP(26 + unit, 128 * unit);
    }
}

}

extern "C" void kernel_launch(void* const* d_in, const int* in_sizes, int n_in, void* d_out, int out_size) {
    const __nv_bfloat16* sv = (const __nv_bfloat16*)d_in[0];
    const __nv_bfloat16* pos = (const __nv_bfloat16*)d_in[1];
    const int* src = (const int*)d_in[2];
    const int* dst = (const int*)d_in[3];
    const __nv_bfloat16* freqs = (const __nv_bfloat16*)d_in[4];
    const __nv_bfloat16* w1 = (const __nv_bfloat16*)d_in[5];
    const __nv_bfloat16* w2 = (const __nv_bfloat16*)d_in[6];
    const __nv_bfloat16* wrbf = (const __nv_bfloat16*)d_in[7];
    __nv_bfloat16* out = (__nv_bfloat16*)d_out;
    const int N = in_sizes[1] / 3;
    const int E = in_sizes[2];

    static bool init = false;
    if (!init) {
        cudaFuncSetAttribute(fused_kernel, cudaFuncAttributeMaxDynamicSharedMemorySize, M_SMEM);
        init = true;
    }
    fused_kernel<<<NCTA, M_THREADS, M_SMEM, cudaStreamPerThread>>>(sv, pos, src, dst, freqs, w1, w2, wrbf, out, N, E);
}
```
